```python
import torch

def _softmax(x, axis=-1):
    return torch.softmax(x, dim=axis)
def _gelu(x):
    return torch.nn.functional.gelu(x, approximate="tanh")
def _silu(x):
    return torch.nn.functional.silu(x)
def _sigmoid(x):
    return torch.sigmoid(x)
def _layernorm(x, axis=-1, eps=1e-5):
    m = x.mean(dim=axis, keepdim=True)
    v = x.var(dim=axis, keepdim=True, unbiased=False)
    return (x - m) / torch.sqrt(v + eps)
def _scatter_add(tgt, idx, src, axis=0):
    return tgt.clone().index_add_(axis, idx, src)
def _segment_sum(src, seg, n):
    out = torch.zeros((n,) + src.shape[1:], dtype=src.dtype)
    return out.index_add_(0, seg, src)
def _pad(x, pw):
    flat = tuple(v for pair in reversed(pw) for v in pair)
    return torch.nn.functional.pad(x, flat)

kernel_name = 'standalone__gqa_block_cached__decode'

def setup_inputs():

    _w = (lambda a: (lambda t: t.to(torch.bfloat16) if t.is_floating_point() else t)(torch.as_tensor(a)))
    B, Sq, D = 1, 1, 576
    Hq, Hkv, Sk, Dh = 32, 16, 65536, 128
    assert Hq % Hkv == 0, (Hq, Hkv)
    return {
        "x": _w((lambda *s: torch.randn(*s, dtype=torch.bfloat16) * 0.8)(B, Sq, D)),
        "k_cache": _w((lambda *s: torch.randn(*s, dtype=torch.bfloat16) * 0.8)(B, Hkv, Sk, Dh)),
        "v_cache": _w((lambda *s: torch.randn(*s, dtype=torch.bfloat16) * 0.05)(B, Hkv, Sk, Dh)),
        "wq": _w((lambda *s: torch.randn(*s, dtype=torch.bfloat16) * 0.8)(D, Hq * Dh) * (D ** -0.5)),
        "wo": _w((lambda *s: torch.randn(*s, dtype=torch.bfloat16) * 0.05)(Hq * Dh, D) * ((Hq * Dh) ** -0.5)),
    }

def reference(x, k_cache, v_cache, wq, wo):
    B, Sq, D = x.shape
    Hq, Dh = 32, 128
    Hkv = k_cache.shape[1]
    rep = Hq // Hkv
    q = (lambda x, *d: x.permute(*d))((x @ wq).reshape(B, Sq, Hq, Dh), 0, 2, 1, 3)
    k = (lambda x, n, axis: torch.repeat_interleave(x, n, dim=axis))(k_cache, rep, axis=1)
    v = (lambda x, n, axis: torch.repeat_interleave(x, n, dim=axis))(v_cache, rep, axis=1)
    scores = torch.einsum("bhqd,bhkd->bhqk", q, k) * (Dh ** -0.5)
    p = _softmax(scores, axis=-1)
    o = torch.einsum("bhqk,bhkd->bhqd", p, v)
    return (lambda x, *d: x.permute(*d))(o, 0, 2, 1, 3).reshape(B, Sq, Hq * Dh) @ wo
```

```cpp
#include <cuda_runtime.h>
#include <cuda_bf16.h>
#include <stdint.h>

namespace {

constexpr int D_MODEL = 576;
constexpr int HQ = 32;
constexpr int HKV = 16;
constexpr int SK = 65536;
constexpr int DH = 128;
constexpr int QCOLS = HQ * DH;

constexpr int TILE_KEYS = 64;
constexpr int TILE_BYTES = TILE_KEYS * DH * 2;
constexpr int TILES_PER_HEAD = SK / TILE_KEYS;
constexpr int NTILES = TILES_PER_HEAD * HKV;
#define GQA_STAGES 6
#define GQA_INFL 3
#define GQA_DIRECT 16
#define GQA_INIT 2
#define GQA_PACE 1500
#define GQA_PFW 2
#define GQA_D1 2500
#define GQA_D2 2000
#define GQA_DEPTH 1
#define GQA_LIFT 0
constexpr int STAGES = GQA_STAGES;
constexpr int INFL = GQA_INFL;
constexpr int INIT = GQA_INIT;
constexpr int DEPTH = GQA_DEPTH;

constexpr int CL = 8;
constexpr int NSR = 5;
constexpr int NAR = CL - NSR;
constexpr int MAX_CL = 16, MIN_CL = 12;
constexpr int NCONS = 4;
constexpr int NTHREADS = 8 * 32;
constexpr int NQITEM = QCOLS / 64;
constexpr int QROWS = D_MODEL / NAR;
constexpr int QLEAD = 2;
constexpr int NOWN = D_MODEL / 16;
constexpr int NSLOT = NSR * NCONS;
constexpr uint32_t MERGE_BYTES = NSLOT * (1024 + 16);

constexpr int SS_STAGE = 0;
constexpr int SS_Q = SS_STAGE + STAGES * 2 * TILE_BYTES;
constexpr int SS_BAR = SS_Q + QCOLS * 2;
constexpr int SS_META = SS_BAR + (2 * STAGES + HKV + NAR) * 8;
constexpr int SS_TOTAL = SS_META + STAGES * 4;
constexpr int SA_WO = 0;
constexpr int SA_SLOT = SA_WO + HKV * 4 * 128 * 16;
constexpr int SA_ML = SA_SLOT + NSLOT * 1024;
constexpr int SA_QRED = SA_ML + 2 * NSLOT * 8;
constexpr int SA_O = SA_QRED + QLEAD * NAR * 8 * 256;
constexpr int SA_ORED = SA_O + HKV * 512;
constexpr int SA_WT = SA_ORED + 16 * 4 * 4;
constexpr int SA_BAR = SA_WT + 4 * 32 * 4;
constexpr int SA_TOTAL = SA_BAR + (1 + QLEAD + HKV) * 8;
constexpr int SM_TOTAL = SS_TOTAL > SA_TOTAL ? SS_TOTAL : SA_TOTAL;

constexpr uint32_t SPIN_LIMIT = 1u << 24;

struct Scratch {
    uint4 part[HKV][MAX_CL][128];
    unsigned long long qpk[QCOLS / 2];
    unsigned int epoch;
    unsigned int pad0[31];
    unsigned int ticket;
    unsigned int pad1[31];
};
__device__ __align__(128) Scratch g_scratch;

#define TRACE(slot) do { } while (0)
#define PROG(t) do { } while (0)

__device__ __forceinline__ uint32_t smem_u32(const void* p) { return (uint32_t)__cvta_generic_to_shared(p); }
__device__ __forceinline__ uint32_t mapa(uint32_t a, uint32_t rank) {
    uint32_t r;
    asm("mapa.shared::cluster.u32 %0, %1, %2;" : "=r"(r) : "r"(a), "r"(rank));
    return r;
}
__device__ __forceinline__ void mbar_init(uint32_t bar, uint32_t cnt) {
    asm volatile("mbarrier.init.shared::cta.b64 [%0], %1;" ::"r"(bar), "r"(cnt) : "memory");
}
__device__ __forceinline__ void mbar_expect_tx(uint32_t bar, uint32_t bytes) {
    asm volatile("mbarrier.arrive.expect_tx.shared::cta.b64 _, [%0], %1;" ::"r"(bar), "r"(bytes) : "memory");
}
__device__ __forceinline__ void mbar_arrive(uint32_t bar) {
    asm volatile("mbarrier.arrive.shared::cta.b64 _, [%0];" ::"r"(bar) : "memory");
}
__device__ __forceinline__ void mbar_arrive_remote(uint32_t cbar) {
    asm volatile("mbarrier.arrive.release.cluster.shared::cluster.b64 _, [%0];" ::"r"(cbar) : "memory");
}
__device__ __forceinline__ bool mbar_try(uint32_t bar, uint32_t parity) {
    uint32_t ok;
    asm volatile(
        "{\n.reg .pred p;\nmbarrier.try_wait.parity.shared::cta.b64 p, [%1], %2;\nselp.u32 %0, 1, 0, p;\n}"
        : "=r"(ok) : "r"(bar), "r"(parity) : "memory");
    return ok != 0;
}
__device__ __forceinline__ void mbar_wait(uint32_t bar, uint32_t parity) {
    uint32_t n = 0;
    while (!mbar_try(bar, parity)) {
        if (++n > SPIN_LIMIT) __trap();
    }
}
__device__ __forceinline__ void cluster_arrive_relaxed() { asm volatile("barrier.cluster.arrive.relaxed.aligned;" ::: "memory"); }
__device__ __forceinline__ void cluster_wait() { asm volatile("barrier.cluster.wait.acquire.aligned;" ::: "memory"); }
__device__ __forceinline__ void st_async_v4(uint32_t caddr, float a, float b, float c, float d, uint32_t cbar) {
    asm volatile("st.async.weak.shared::cluster.mbarrier::complete_tx::bytes.v4.f32 [%0], {%1,%2,%3,%4}, [%5];"
                 ::"r"(caddr), "f"(a), "f"(b), "f"(c), "f"(d), "r"(cbar) : "memory");
}
__device__ __forceinline__ void st_async_v2(uint32_t caddr, uint32_t a, uint32_t b, uint32_t cbar) {
    asm volatile("st.async.weak.shared::cluster.mbarrier::complete_tx::bytes.v2.b32 [%0], {%1,%2}, [%3];"
                 ::"r"(caddr), "r"(a), "r"(b), "r"(cbar) : "memory");
}
__device__ __forceinline__ void st_async_b32(uint32_t caddr, uint32_t a, uint32_t cbar) {
    asm volatile("st.async.weak.shared::cluster.mbarrier::complete_tx::bytes.b32 [%0], %1, [%2];"
                 ::"r"(caddr), "r"(a), "r"(cbar) : "memory");
}
__device__ __forceinline__ void bulk_load(uint32_t dst, const void* src, uint32_t bytes, uint32_t bar, uint64_t pol) {
    asm volatile(
        "cp.async.bulk.shared::cluster.global.mbarrier::complete_tx::bytes.L2::cache_hint [%0], [%1], %2, [%3], %4;"
        ::"r"(dst), "l"(src), "r"(bytes), "r"(bar), "l"(pol) : "memory");
}
__device__ __forceinline__ void l2_prefetch(const void* src, uint32_t bytes) {
    asm volatile("cp.async.bulk.prefetch.L2.global [%0], %1;" ::"l"(src), "r"(bytes) : "memory");
}
__device__ __forceinline__ void cp_async16(uint32_t dst, const void* src) {
    asm volatile("cp.async.cg.shared.global.L2::128B [%0], [%1], 16;" ::"r"(dst), "l"(src) : "memory");
}
__device__ __forceinline__ uint4 lds128(uint32_t a) {
    uint4 v;
    asm volatile("ld.shared.v4.u32 {%0,%1,%2,%3}, [%4];" : "=r"(v.x), "=r"(v.y), "=r"(v.z), "=r"(v.w) : "r"(a) : "memory");
    return v;
}
__device__ __forceinline__ uint4 ldsm_x4_trans(uint32_t a) {
    uint4 v;
    asm volatile("ldmatrix.sync.aligned.m8n8.x4.trans.shared.b16 {%0,%1,%2,%3}, [%4];"
                 : "=r"(v.x), "=r"(v.y), "=r"(v.z), "=r"(v.w) : "r"(a) : "memory");
    return v;
}
__device__ __forceinline__ void mma_bf16(float (&c)[4], uint32_t a0, uint32_t a1, uint32_t a2, uint32_t a3,
                                         uint32_t b0, uint32_t b1) {
    asm volatile(
        "mma.sync.aligned.m16n8k16.row.col.f32.bf16.bf16.f32 {%0,%1,%2,%3}, {%4,%5,%6,%7}, {%8,%9}, {%0,%1,%2,%3};"
        : "+f"(c[0]), "+f"(c[1]), "+f"(c[2]), "+f"(c[3])
        : "r"(a0), "r"(a1), "r"(a2), "r"(a3), "r"(b0), "r"(b1));
}
__device__ __forceinline__ uint4 ldg_nc128(const void* p) {
    uint4 v;
    asm volatile("ld.global.nc.L1::no_allocate.L2::128B.v4.u32 {%0,%1,%2,%3}, [%4];"
                 : "=r"(v.x), "=r"(v.y), "=r"(v.z), "=r"(v.w) : "l"(p));
    return v;
}
__device__ __forceinline__ uint32_t ld_relaxed32(const void* p) {
    uint32_t v;
    asm volatile("ld.relaxed.gpu.global.b32 %0, [%1];" : "=r"(v) : "l"(p) : "memory");
    return v;
}
__device__ __forceinline__ void st_relaxed64(void* p, unsigned long long v) {
    asm volatile("st.relaxed.gpu.global.b64 [%0], %1;" ::"l"(p), "l"(v) : "memory");
}
__device__ __forceinline__ void ld_relaxed64x2(const void* p, unsigned long long& lo, unsigned long long& hi) {
    asm volatile("ld.relaxed.gpu.global.v2.b64 {%0, %1}, [%2];" : "=l"(lo), "=l"(hi) : "l"(p) : "memory");
}
__device__ __forceinline__ void ld_relaxed128(const void* p, unsigned long long& lo, unsigned long long& hi) {
    asm volatile("{\n.reg .b128 t;\nld.relaxed.gpu.global.b128 t, [%2];\nmov.b128 {%0, %1}, t;\n}"
                 : "=l"(lo), "=l"(hi) : "l"(p) : "memory");
}
__device__ __forceinline__ void st_relaxed128(void* p, unsigned long long lo, unsigned long long hi) {
    asm volatile("{\n.reg .b128 t;\nmov.b128 t, {%1, %2};\nst.relaxed.gpu.global.b128 [%0], t;\n}"
                 ::"l"(p), "l"(lo), "l"(hi) : "memory");
}
__device__ __forceinline__ float ex2(float x) {
    float y;
    asm("ex2.approx.ftz.f32 %0, %1;" : "=f"(y) : "f"(x));
    return y;
}
__device__ __forceinline__ float rcp(float x) {
    float y;
    asm("rcp.approx.ftz.f32 %0, %1;" : "=f"(y) : "f"(x));
    return y;
}
__device__ __forceinline__ float warp_max(float v) {
    int k = __float_as_int(v);
    k ^= (k >> 31) & 0x7fffffff;
    k = __reduce_max_sync(0xffffffffu, k);
    k ^= (k >> 31) & 0x7fffffff;
    return __int_as_float(k);
}
__device__ __forceinline__ uint32_t pack_bf16(float lo, float hi) {
    uint32_t r;
    asm("cvt.rn.bf16x2.f32 %0, %1, %2;" : "=r"(r) : "f"(hi), "f"(lo));
    return r;
}
__device__ __forceinline__ float bf_lo(uint32_t v) { return __uint_as_float(v << 16); }
__device__ __forceinline__ float bf_hi(uint32_t v) { return __uint_as_float(v & 0xffff0000u); }
__device__ __forceinline__ void named_sync(int id, int n) { asm volatile("bar.sync %0, %1;" ::"r"(id), "r"(n) : "memory"); }
__device__ __forceinline__ void fma8(float* a, float s, const uint4& w) {
    a[0] = fmaf(s, bf_lo(w.x), a[0]); a[1] = fmaf(s, bf_hi(w.x), a[1]);
    a[2] = fmaf(s, bf_lo(w.y), a[2]); a[3] = fmaf(s, bf_hi(w.y), a[3]);
    a[4] = fmaf(s, bf_lo(w.z), a[4]); a[5] = fmaf(s, bf_hi(w.z), a[5]);
    a[6] = fmaf(s, bf_lo(w.w), a[6]); a[7] = fmaf(s, bf_hi(w.w), a[7]);
}

__global__ void __cluster_dims__(CL, 1, 1) __launch_bounds__(NTHREADS, 1)
gqa_decode_kernel(int ncl, uint32_t zero, const __nv_bfloat16* __restrict__ kc, const __nv_bfloat16* __restrict__ vc,
                  const __nv_bfloat16* __restrict__ wq, const __nv_bfloat16* __restrict__ x, Scratch* __restrict__ sc,
                  const __nv_bfloat16* __restrict__ wo, __nv_bfloat16* __restrict__ out) {
    extern __shared__ __align__(1024) unsigned char smem[];
    const uint32_t sb = smem_u32(smem);
    const int tid = threadIdx.x, warp = tid >> 5, lane = tid & 31;
    const int rank = blockIdx.x % CL, cl = blockIdx.x / CL;
    constexpr float SCL = 0.08838834764831845f * 1.4426950408889634f;

    if (rank < NSR) {
        const uint32_t bar_full = sb + SS_BAR, bar_empty = bar_full + STAGES * 8;
        const uint32_t bar_q = bar_empty + STAGES * 8, bar_free = bar_q + HKV * 8;
        volatile uint32_t* meta = reinterpret_cast<volatile uint32_t*>(smem + SS_META);
        if (warp > NCONS + 1) return;
        if (warp == NCONS + 1) {
            const uint32_t tag = ld_relaxed32(&sc->epoch) + 1u;
            if (lane == 0) {
#pragma unroll
                for (int a = 0; a < NAR; a++) mbar_init(bar_free + a * 8, 1);
#pragma unroll
                for (int h = 0; h < HKV; h++) mbar_init(bar_q + h * 8, 32);
                asm volatile("fence.mbarrier_init.release.cluster;" ::: "memory");
            }
            __syncwarp();
            asm volatile("bar.arrive 1, %0;" ::"n"((NCONS + 2) * 32) : "memory");
            cluster_arrive_relaxed();
#pragma unroll 1
            for (int h = 0; h < HKV; h++) {
                unsigned long long lo[2], hi[2];
                uint32_t n = 0;
                while (true) {
                    bool ok = true;
#pragma unroll
                    for (int k = 0; k < 2; k++) {
                        ld_relaxed64x2(&sc->qpk[h * 128 + (k * 32 + lane) * 2], lo[k], hi[k]);
                        ok = ok && ((uint32_t)(lo[k] >> 32) == tag) && ((uint32_t)(hi[k] >> 32) == tag);
                    }
                    if (ok) break;
                    if (h > 0) __nanosleep(500);
                    if (++n > SPIN_LIMIT) __trap();
                }
#pragma unroll
                for (int k = 0; k < 2; k++)
                    *reinterpret_cast<uint2*>(smem + SS_Q + h * 512 + (k * 32 + lane) * 8) = make_uint2((uint32_t)lo[k], (uint32_t)hi[k]);
                mbar_arrive(bar_q + h * 8);
            }
            return;
        }
        if (warp == NCONS) {
            const int ns = ncl * NSR, sid = cl * NSR + rank;
            uint64_t pol = 0;
            const char* kp = reinterpret_cast<const char*>(kc);
            const char* vp = reinterpret_cast<const char*>(vc);
            auto issue = [&](int i, int s, int t) {
                PROG(t);
                mbar_expect_tx(bar_full + s * 8, 2 * TILE_BYTES);
                bulk_load(sb + SS_STAGE + s * 2 * TILE_BYTES, kp + (size_t)t * TILE_BYTES, TILE_BYTES, bar_full + s * 8, pol);
                bulk_load(sb + SS_STAGE + s * 2 * TILE_BYTES + TILE_BYTES, vp + (size_t)t * TILE_BYTES, TILE_BYTES, bar_full + s * 8, pol);
                meta[s] = ((uint32_t)(i + 1) << 5) | (uint32_t)(t / TILES_PER_HEAD);
            };
            if (lane == 0) TRACE(0);
            if (lane < STAGES) meta[lane] = 0;
            __syncwarp();
            long long t_start = 0;
            if (lane == 0) {
#pragma unroll
                for (int s = 0; s < STAGES; s++) {
                    mbar_init(bar_full + s * 8, 1);
                    mbar_init(bar_empty + s * 8, NCONS);
                }
                asm volatile("fence.proxy.async.shared::cta;" ::: "memory");
                asm volatile("createpolicy.fractional.L2::evict_first.b64 %0, 1.0;" : "=l"(pol));
                t_start = clock64();
#pragma unroll
                for (int s = 0; s < INIT; s++) issue(s, s, sid + s * ns);
                TRACE(1);
            }
            __syncwarp();
            asm volatile("bar.arrive 1, %0;" ::"n"((NCONS + 2) * 32) : "memory");
            cluster_arrive_relaxed();
            if (lane == 0) {
#pragma unroll 1
                for (int s = INIT; s < STAGES; s++) {
                    while (clock64() - t_start < (long long)(s - INIT + 1) * GQA_PACE) { }
                    issue(s, s, sid + s * ns);
                }
                const int base = (STAGES + DEPTH) * ns;
                int tk[DEPTH];
#pragma unroll
                for (int j = 0; j < DEPTH; j++) tk[j] = sid + (STAGES + j) * ns;
                int i = STAGES;
                int s = 0;
                uint32_t ph = 1;
                int sp = STAGES - INFL;
                uint32_t php = 0;
                const int lift = NTILES - GQA_LIFT * ns;
                bool done = false;
                while (!done) {
#pragma unroll
                    for (int j = 0; j < DEPTH; j++) {
                        if (done) break;
                        mbar_wait(bar_empty + s * 8, ph ^ 1);
                        const int t = tk[j];
                        if (t >= NTILES) {
                            int any = 0;
#pragma unroll
                            for (int k = 0; k < DEPTH; k++) any |= tk[k];
                            meta[s] = ((uint32_t)(i + 1) << 5) | (uint32_t)(HKV + (any < 0));
                            done = true;
                            break;
                        }
                        if (t < lift) mbar_wait(bar_full + sp * 8, php);
                        issue(i, s, t);
                        tk[j] = base + (int)atomicAdd(&sc->ticket, 1u);
                        i++;
                        if (++s == STAGES) { s = 0; ph ^= 1; }
                        if (++sp == STAGES) { sp = 0; php ^= 1; }
                    }
                }
            }
            return;
        }
        cluster_arrive_relaxed();
        const int g = lane >> 2, t4 = lane & 3;
        const uint32_t koff = warp * 16 * 256 + g * 256 + t4 * 16 + (g & 1) * 64;
        const uint32_t qoff = (g >> 2) * 256 + t4 * 16 + (((g >> 1) ^ g) & 1) * 64;
        const bool odd = ((g ^ t4) & 1) != 0;
        const int kk = lane & 7, mi = lane >> 3;
        const uint32_t voff = TILE_BYTES + warp * 16 * 256 + (2 * (kk >> 1) + (mi >> 1) + 8 * (kk & 1)) * 256 +
                              (mi & 1) * 16 + (kk >> 1) * 32;
        const int src0 = 8 * t4 + 2 * (g >> 2);
        const bool bnz = (t4 == (g & 3));
        const int slot = rank * NCONS + warp;
        const uint32_t poff = SA_SLOT + slot * 1024 + (t4 >> 1) * 512 + (g * 2 + (t4 & 1)) * 16;
        named_sync(1, (NCONS + 2) * 32);

        int s = 0;
        uint32_t ph = 0, seq = 1;
        int th = 0;
        for (int h = 0; h < HKV; h++) {
            mbar_wait(bar_q + h * 8, 0);
            if (h == 0 && tid == 0) TRACE(3);
            uint4 qf[4];
#pragma unroll
            for (int j = 0; j < 4; j++) qf[j] = lds128(sb + SS_Q + h * 512 + (qoff ^ (j * 64)));
            float acc[8][4];
#pragma unroll
            for (int i = 0; i < 8; i++) { acc[i][0] = acc[i][1] = acc[i][2] = acc[i][3] = 0.f; }
            float m = -INFINITY, l = 0.f;
            if (h == 0) cluster_wait();
            if (h >= NAR) mbar_wait(bar_free + (h % NAR) * 8, (uint32_t)(h / NAR - 1) & 1u);
            const uint32_t rb_ = mapa(sb, NSR + h % NAR);
            while (th == h) {
                const uint32_t st = sb + SS_STAGE + s * 2 * TILE_BYTES;
                mbar_wait(bar_full + s * 8, ph);
                const int sn = (s + 1 == STAGES) ? 0 : s + 1;
                uint32_t mt = meta[sn];
                float c0[4] = {0.f, 0.f, 0.f, 0.f}, c1[4] = {0.f, 0.f, 0.f, 0.f};
                uint4 ra[4], rb[4];
#pragma unroll
                for (int j = 0; j < 4; j++) {
                    ra[j] = lds128(st + (koff ^ (j * 64)));
                    rb[j] = lds128(st + (koff ^ (j * 64)) + 8 * 256);
                }
                uint4 va[8];
#pragma unroll
                for (int i = 0; i < 8; i++) va[i] = ldsm_x4_trans(st + (voff ^ (i * 32)));
                {
                    uint32_t dep = (ra[0].x | rb[0].x | ra[1].x) | (rb[1].x | ra[2].x | rb[2].x) | (ra[3].x | rb[3].x | va[0].x) |
                                   (va[1].x | va[2].x | va[3].x) | (va[4].x | va[5].x | va[6].x) | va[7].x;
                    if (lane == 0) mbar_arrive(bar_empty + s * 8 + (dep & zero));
                }
#pragma unroll
                for (int j = 0; j < 4; j++) {
                    mma_bf16(c0, ra[j].x, rb[j].x, ra[j].y, rb[j].y, qf[j].x, qf[j].y);
                    mma_bf16(c1, ra[j].z, rb[j].z, ra[j].w, rb[j].w, qf[j].z, qf[j].w);
                }
                const float sa = odd ? (c0[1] + c1[1]) : (c0[0] + c1[0]);
                const float sc = odd ? (c0[3] + c1[3]) : (c0[2] + c1[2]);
                float mx = fmaxf(sa, sc);
                mx = fmaxf(mx, __shfl_xor_sync(0xffffffffu, mx, 4));
                mx = fmaxf(mx, __shfl_xor_sync(0xffffffffu, mx, 8));
                mx = fmaxf(mx, __shfl_xor_sync(0xffffffffu, mx, 16));
                const float mn = fmaxf(m, mx);
                const float alpha = ex2((m - mn) * SCL);
                const float pa = ex2((sa - mn) * SCL);
                const float pb = ex2((sc - mn) * SCL);
                m = mn;
                l = fmaf(l, alpha, pa + pb);
                const uint32_t pk = pack_bf16(pa, pb);
                uint32_t b0 = __shfl_sync(0xffffffffu, pk, src0);
                uint32_t b1 = __shfl_sync(0xffffffffu, pk, src0 + 4);
                b0 = bnz ? b0 : 0u;
                b1 = bnz ? b1 : 0u;
#pragma unroll
                for (int i = 0; i < 8; i++) {
                    acc[i][0] *= alpha; acc[i][1] *= alpha; acc[i][2] *= alpha; acc[i][3] *= alpha;
                    mma_bf16(acc[i], va[i].x, va[i].y, va[i].z, va[i].w, b0, b1);
                }
                s = sn;
                if (s == 0) ph ^= 1;
                seq++;
                uint32_t n = 0;
                while ((mt >> 5) != seq) {
                    mt = meta[s];
                    if (++n > SPIN_LIMIT) __trap();
                }
                th = (int)(mt & 31u);
            }
            l += __shfl_xor_sync(0xffffffffu, l, 4);
            l += __shfl_xor_sync(0xffffffffu, l, 8);
            l += __shfl_xor_sync(0xffffffffu, l, 16);
            float w[8];
#pragma unroll
            for (int k = 0; k < 4; k++) {
                const int i = (k & 1) | ((k & 2) << 1);
                w[2 * k] = (acc[i][0] + acc[i ^ 1][1]) + __shfl_xor_sync(0xffffffffu, acc[i ^ 2][0] + acc[i ^ 3][1], 1);
                w[2 * k + 1] = (acc[i][2] + acc[i ^ 1][3]) + __shfl_xor_sync(0xffffffffu, acc[i ^ 2][2] + acc[i ^ 3][3], 1);
            }
            st_async_v4(rb_ + poff, w[0], w[1], w[2], w[3], rb_ + SA_BAR);
            st_async_v4(rb_ + poff + 256, w[4], w[5], w[6], w[7], rb_ + SA_BAR);
            if (g == 0 && (t4 & 1) == 0)
                st_async_v2(rb_ + SA_ML + ((t4 >> 1) * NSLOT + slot) * 8, __float_as_uint(m), __float_as_uint(l), rb_ + SA_BAR);
            if (tid == 0) TRACE(16 + h);
        }
        return;
    }

    const int ar = rank - NSR, aid = cl * NAR + ar;
    const uint32_t bar_merge = sb + SA_BAR, bar_qred = bar_merge + 8, bar_o = bar_qred + QLEAD * 8;
    if (tid == 0) TRACE(4);
    const uint32_t tag = ld_relaxed32(&sc->epoch) + 1u;
    {
        const int row0 = ar * QROWS + (tid >> 3);
        const __nv_bfloat16* wp = wq + (size_t)row0 * QCOLS + (tid & 7) * 8;
        uint4 w[6];
#pragma unroll
        for (int i = 0; i < 6; i++) w[i] = ldg_nc128(wp + cl * 64 + (size_t)i * 32 * QCOLS);
        float xv[6];
#pragma unroll
        for (int i = 0; i < 6; i++) xv[i] = __bfloat162float(x[row0 + i * 32]);
        if (tid == 7 * 32) {
            mbar_init(bar_merge, 1);
#pragma unroll
            for (int k = 0; k < QLEAD; k++) mbar_init(bar_qred + k * 8, 1);
#pragma unroll
            for (int h = 0; h < HKV; h++) mbar_init(bar_o + h * 8, 1);
            asm volatile("fence.mbarrier_init.release.cluster;" ::: "memory");
            mbar_expect_tx(bar_merge, MERGE_BYTES);
#pragma unroll
            for (int k = 0; k < QLEAD; k++) mbar_expect_tx(bar_qred + k * 8, NAR * 8 * 256);
#pragma unroll
            for (int h = 0; h < HKV; h++) mbar_expect_tx(bar_o + h * 8, 512);
        }
        __syncwarp();
        cluster_arrive_relaxed();
        cluster_wait();
        int rnd = 0;
#pragma unroll 1
        for (int c = cl; c < NQITEM; c += ncl, rnd++) {
            if (rnd > 0) {
#pragma unroll
                for (int i = 0; i < 6; i++) w[i] = ldg_nc128(wp + c * 64 + (size_t)i * 32 * QCOLS);
            }
            float a[8];
#pragma unroll
            for (int k = 0; k < 8; k++) a[k] = 0.f;
#pragma unroll
            for (int i = 0; i < 6; i++) fma8(a, xv[i], w[i]);
            const bool u4 = lane & 16, u3 = lane & 8;
            float r4[4], r2[2];
#pragma unroll
            for (int k = 0; k < 4; k++)
                r4[k] = (u4 ? a[k + 4] : a[k]) + __shfl_xor_sync(0xffffffffu, u4 ? a[k] : a[k + 4], 16);
#pragma unroll
            for (int k = 0; k < 2; k++)
                r2[k] = (u3 ? r4[k + 2] : r4[k]) + __shfl_xor_sync(0xffffffffu, u3 ? r4[k] : r4[k + 2], 8);
            const int lead = rnd % NAR, lk = rnd / NAR;
            const uint32_t rb_ = mapa(sb, NSR + lead) + (tag & zero);
            st_async_v2(rb_ + SA_QRED + lk * (NAR * 8 * 256) + (ar * 8 + warp) * 256 + ((lane & 7) * 4 + (lane >> 3)) * 8,
                        __float_as_uint(r2[0]), __float_as_uint(r2[1]), rb_ + SA_BAR + 8 + lk * 8);
            if (lead == ar) {
                if (warp == 0) {
                    mbar_wait(bar_qred + lk * 8, 0);
                    float s0 = 0.f, s1 = 0.f;
#pragma unroll
                    for (int k = 0; k < NAR * 8; k++) {
                        const float2 v = *reinterpret_cast<const float2*>(smem + SA_QRED + lk * (NAR * 8 * 256) + k * 256 + lane * 8);
                        s0 += v.x; s1 += v.y;
                    }
                    st_relaxed64(&sc->qpk[c * 32 + lane], (unsigned long long)pack_bf16(s0, s1) | ((unsigned long long)tag << 32));
                    if (rnd == 0 && lane == 0) TRACE(2);
                }
                named_sync(1, 256);
            }
            if (rnd == 0) {
                __nanosleep(GQA_D1);
                if (warp == 1) {
                    for (int r = aid + lane * ncl * NAR; r < D_MODEL; r += ncl * NAR * 32)
                        l2_prefetch(wq + (size_t)r * QCOLS + ncl * 64, (QCOLS - ncl * 64) * 2);
                    for (int r = aid + lane * ncl * NAR; r < D_MODEL; r += ncl * NAR * 32) l2_prefetch(wo + (size_t)r * QCOLS, QCOLS * 2);
                }
                __nanosleep(GQA_D2);
            }
        }
    }
    const int j = tid & 127;
    if (warp < 4) {
        float* wbuf = reinterpret_cast<float*>(smem + SA_WT) + warp * 32;
        uint4* dst = &sc->part[ar][cl][j];
        uint32_t ph = 0;
#pragma unroll 1
        for (int h = ar; h < HKV; h += NAR, dst += NAR * MAX_CL * 128) {
            mbar_wait(bar_merge, ph);
            ph ^= 1;
            float2 e = make_float2(-INFINITY, 0.f);
            if (lane < NSLOT) e = *reinterpret_cast<const float2*>(smem + SA_ML + ((warp >> 1) * NSLOT + lane) * 8);
            float2 u[NSLOT];
#pragma unroll
            for (int k = 0; k < NSLOT; k++) u[k] = *reinterpret_cast<const float2*>(smem + SA_SLOT + k * 1024 + j * 8);
            float M = warp_max(e.x);
            const bool none = (M == -INFINITY);
            if (none) M = 0.f;
            const float wt = ex2((e.x - M) * SCL);
            wbuf[lane] = wt;
            __syncwarp();
            float L = wt * e.y;
#pragma unroll
            for (int o = 16; o > 0; o >>= 1) L += __shfl_xor_sync(0xffffffffu, L, o);
            float o0 = 0.f, o1 = 0.f, p0 = 0.f, p1 = 0.f;
#pragma unroll
            for (int k = 0; k < NSLOT / 4; k++) {
                const float4 w4 = *reinterpret_cast<const float4*>(wbuf + k * 4);
                o0 = fmaf(w4.x, u[4 * k].x, o0);     o1 = fmaf(w4.x, u[4 * k].y, o1);
                p0 = fmaf(w4.y, u[4 * k + 1].x, p0); p1 = fmaf(w4.y, u[4 * k + 1].y, p1);
                o0 = fmaf(w4.z, u[4 * k + 2].x, o0); o1 = fmaf(w4.z, u[4 * k + 2].y, o1);
                p0 = fmaf(w4.w, u[4 * k + 3].x, p0); p1 = fmaf(w4.w, u[4 * k + 3].y, p1);
            }
            const float inv = none ? 0.f : rcp(L);
            const float lse = none ? -INFINITY : fmaf(M, SCL, __log2f(L));
            st_relaxed128(dst,
                          (unsigned long long)__float_as_uint(lse) | ((unsigned long long)__float_as_uint((o0 + p0) * inv) << 32),
                          (unsigned long long)__float_as_uint((o1 + p1) * inv) | ((unsigned long long)tag << 32));
            if (tid == 0) TRACE(32 + h);
            if (h + NAR < HKV) {
                named_sync(2, 128);
                if (tid == 0) mbar_expect_tx(bar_merge, MERGE_BYTES);
                __syncwarp();
                if (tid < NSR) mbar_arrive_remote(mapa(sb + SS_BAR + (2 * STAGES + HKV + ar) * 8, tid));
            }
        }
    } else if (aid < NOWN) {
        const int ow = warp - 4;
        {
            auto row_of = [](int p) {
                return (p >> 6) * 128 + 16 * ((((p >> 3) & 4) | (p & 1)) ^ (p & 2)) + ((p >> 2) & 7);
            };
            const int pa = ow * 32 + (lane >> 1), ch = lane & 1;
            const __nv_bfloat16* wa = wo + (size_t)row_of(pa) * D_MODEL + aid * 16 + ch * 8;
            const __nv_bfloat16* wb = wo + (size_t)row_of(pa + 16) * D_MODEL + aid * 16 + ch * 8;
#pragma unroll 1
            for (int h = 0; h < HKV; h++) {
                const uint32_t dst = sb + SA_WO + (h * 4 + ch) * 2048 + pa * 16;
                cp_async16(dst, wa);
                cp_async16(dst + 256, wb);
                cp_async16(dst + 4096, wa + 8 * D_MODEL);
                cp_async16(dst + 4096 + 256, wb + 8 * D_MODEL);
                wa += 256 * D_MODEL;
                wb += 256 * D_MODEL;
            }
            asm volatile("cp.async.commit_group;" ::: "memory");
            asm volatile("cp.async.wait_group 0;" ::: "memory");
            __syncwarp();
        }
        const int par = lane & 1;
        const int pj = (ar == 0 ? 0 : 2 + 42 * ar) + ow * 11 + (lane >> 1);
        const bool comb = lane < 22 && pj < (ar == 2 ? 128 : 44 + 42 * ar);
        const uint32_t cmask = __ballot_sync(0xffffffffu, comb);
        const bool has6 = 12 + par < ncl, has7 = 14 + par < ncl;
        const uint4* src = &sc->part[0][par][comb ? pj : 0];
        const int off6 = has6 ? 6 * 256 : 0, off7 = has7 ? 7 * 256 : 0;
        const uint32_t oaddr = SA_O + pj * 4;
        const uint32_t aoff = SA_WO + ((lane & 1) * 2 + ((lane >> 3) & 1)) * 2048 + (ow * 32 + ((lane >> 1) & 3) * 8 + (lane >> 4)) * 16;
        const uint32_t boff = SA_O + (ow * 32 + (lane & 3) * 8) * 4;
        float acc0[4] = {0.f, 0.f, 0.f, 0.f}, acc1[4] = {0.f, 0.f, 0.f, 0.f};
#pragma unroll 1
        for (int h = 0; h < HKV; h++, src += MAX_CL * 128) {
            uint4 wf[4];
#pragma unroll
            for (int i = 0; i < 4; i++) wf[i] = ldsm_x4_trans(sb + aoff + h * 8192 + i * 32);
            if (comb) {
                unsigned long long lo[8], hi[8];
                uint32_t n = 0;
                while (true) {
#pragma unroll
                    for (int k = 0; k < 6; k++) ld_relaxed128(src + k * 256, lo[k], hi[k]);
                    ld_relaxed128(src + off6, lo[6], hi[6]);
                    ld_relaxed128(src + off7, lo[7], hi[7]);
                    uint32_t bad = 0;
#pragma unroll
                    for (int k = 0; k < 8; k++) bad |= (uint32_t)(hi[k] >> 32) ^ tag;
                    if (__all_sync(cmask, bad == 0)) break;
                    if (h < HKV - 1) __nanosleep(500);
                    if (++n > SPIN_LIMIT) __trap();
                }
                if (lane == 0 && warp < 6) TRACE(4 + warp);
                float e[8];
#pragma unroll
                for (int k = 0; k < 8; k++) e[k] = __uint_as_float((uint32_t)lo[k]);
                if (!has6) e[6] = -INFINITY;
                if (!has7) e[7] = -INFINITY;
                float mx = fmaxf(fmaxf(fmaxf(e[0], e[1]), fmaxf(e[2], e[3])), fmaxf(fmaxf(e[4], e[5]), fmaxf(e[6], e[7])));
                mx = fmaxf(mx, __shfl_xor_sync(cmask, mx, 1));
                float W = 0.f, o0 = 0.f, o1 = 0.f, W2 = 0.f, p0 = 0.f, p1 = 0.f;
#pragma unroll
                for (int k = 0; k < 8; k += 2) {
                    const float wa = ex2(e[k] - mx), wb = ex2(e[k + 1] - mx);
                    W += wa;
                    o0 = fmaf(wa, __uint_as_float((uint32_t)(lo[k] >> 32)), o0);
                    o1 = fmaf(wa, __uint_as_float((uint32_t)hi[k]), o1);
                    W2 += wb;
                    p0 = fmaf(wb, __uint_as_float((uint32_t)(lo[k + 1] >> 32)), p0);
                    p1 = fmaf(wb, __uint_as_float((uint32_t)hi[k + 1]), p1);
                }
                W += W2; o0 += p0; o1 += p1;
                W += __shfl_xor_sync(cmask, W, 1);
                o0 += __shfl_xor_sync(cmask, o0, 1);
                o1 += __shfl_xor_sync(cmask, o1, 1);
                const float inv = rcp(W);
                const uint32_t ob = pack_bf16(o0 * inv, o1 * inv);
                const uint32_t r0 = mapa(sb, NSR + par);
                st_async_b32(r0 + oaddr + h * 512, ob, r0 + SA_BAR + (1 + QLEAD + h) * 8);
                if (par == 0) {
                    const uint32_t r2 = mapa(sb, NSR + 2);
                    st_async_b32(r2 + oaddr + h * 512, ob, r2 + SA_BAR + (1 + QLEAD + h) * 8);
                }
            }
            __syncwarp();
            mbar_wait(bar_o + h * 8, 0);
            const uint4 b0 = lds128(sb + boff + h * 512), b1 = lds128(sb + boff + h * 512 + 16);
            mma_bf16(acc0, wf[0].x, wf[0].y, wf[0].z, wf[0].w, b0.x, b0.y);
            mma_bf16(acc1, wf[1].x, wf[1].y, wf[1].z, wf[1].w, b0.z, b0.w);
            mma_bf16(acc0, wf[2].x, wf[2].y, wf[2].z, wf[2].w, b1.x, b1.y);
            mma_bf16(acc1, wf[3].x, wf[3].y, wf[3].z, wf[3].w, b1.z, b1.w);
        }
        float* ored = reinterpret_cast<float*>(smem + SA_ORED);
        if ((lane & 3) == 0) {
            ored[(lane >> 2) * 4 + ow] = acc0[0] + acc1[0];
            ored[(8 + (lane >> 2)) * 4 + ow] = acc0[2] + acc1[2];
        }
        named_sync(3, 128);
        if (j < 16) {
            const float4 v = *reinterpret_cast<const float4*>(ored + j * 4);
            out[aid * 16 + j] = __float2bfloat16((v.x + v.y) + (v.z + v.w));
        }
        if (j == 0) TRACE(63);
        if (aid == 0 && j == 0) {
            *reinterpret_cast<volatile unsigned int*>(&sc->epoch) = tag;
            *reinterpret_cast<volatile unsigned int*>(&sc->ticket) = 0u;
        }
    }
}

}

extern "C" void kernel_launch(void* const* d_in, const int* in_sizes, int n_in, void* d_out, int out_size) {
    (void)in_sizes; (void)n_in; (void)out_size;
    static int ncl = 0;
    static Scratch* scratch = nullptr;
    cudaLaunchConfig_t cfg = {};
    cudaLaunchAttribute at[1];
    at[0].id = cudaLaunchAttributeClusterDimension;
    at[0].val.clusterDim.x = CL;
    at[0].val.clusterDim.y = 1;
    at[0].val.clusterDim.z = 1;
    cfg.attrs = at;
    cfg.numAttrs = 1;
    cfg.blockDim = dim3(NTHREADS);
    cfg.dynamicSmemBytes = SM_TOTAL;
    cfg.stream = cudaStreamPerThread;
    if (ncl == 0) {
        cudaFuncSetAttribute(gqa_decode_kernel, cudaFuncAttributeMaxDynamicSharedMemorySize, SM_TOTAL);
        cudaGetSymbolAddress((void**)&scratch, g_scratch);
        cfg.gridDim = dim3(MAX_CL * CL);
        int n = 0;
        cudaOccupancyMaxActiveClusters(&n, gqa_decode_kernel, &cfg);
        ncl = n > MAX_CL ? MAX_CL : n;
        if (ncl < MIN_CL) ncl = -1;
    }
    if (ncl < 0) return;
    cfg.gridDim = dim3(ncl * CL);
    cudaLaunchKernelEx(&cfg, gqa_decode_kernel, ncl, 0u, (const __nv_bfloat16*)d_in[1], (const __nv_bfloat16*)d_in[2],
                       (const __nv_bfloat16*)d_in[3], (const __nv_bfloat16*)d_in[0], scratch,
                       (const __nv_bfloat16*)d_in[4], (__nv_bfloat16*)d_out);
}
```

```cpp
#include <cuda_runtime.h>
#include <cuda.h>
#include <cuda_bf16.h>
#include <stdint.h>

namespace {

constexpr int D_MODEL = 576;
constexpr int HQ = 32;
constexpr int HKV = 16;
constexpr int SK = 65536;
constexpr int DH = 128;
constexpr int QCOLS = HQ * DH;

constexpr int TILE_KEYS = 64;
constexpr int TILE_BYTES = TILE_KEYS * DH * 2;
constexpr int TILES_PER_HEAD = SK / TILE_KEYS;
constexpr int NTILES = TILES_PER_HEAD * HKV;
#define GQA_STAGES 6
#define GQA_INFL 3
#define GQA_INIT 1
#define GQA_PACE 1300
#define GQA_D1 4000
#define GQA_D2 2000
#define GQA_PFIRST 1
#define GQA_NPAIR 3
#define GQA_DEFK 2
#define GQA_TRIGW 2
#define GQA_PFN 3
#define GQA_HINT 1000
#define GQA_LIFT 0
constexpr int STAGES = GQA_STAGES;
constexpr int INFL = GQA_INFL;
constexpr int INIT = GQA_INIT;

constexpr int CL = 8;
constexpr int NSR = 5;
constexpr int NAR = CL - NSR;
constexpr int MAX_CL = 16, MIN_CL = 12;
constexpr int NPAIR = GQA_NPAIR;
constexpr int NCONS = 2 * NPAIR;
constexpr int NTHREADS = 8 * 32;
constexpr int NQITEM = QCOLS / 64;
constexpr int QROWS = D_MODEL / NAR;
constexpr int QLEAD = 2;
constexpr int NOWN = D_MODEL / 16;
constexpr int NSLOT = NSR * NCONS;
constexpr uint32_t MERGE_BYTES = NSLOT * 1024, ML_BYTES = NSLOT * 16;

constexpr int SS_STAGE = 0;
constexpr int STAGE_BYTES = 2 * TILE_BYTES;
constexpr int SS_Q = SS_STAGE + STAGES * STAGE_BYTES;
constexpr int DEFK = GQA_DEFK;
constexpr int DEF = DEFK * NSR;
constexpr int SS_O = SS_Q + QCOLS * 2;
constexpr int SS_BAR = SS_O + 3 * 512;
constexpr int SS_BARO = SS_BAR + (3 * STAGES + HKV + NAR) * 8;
constexpr int METAS = 16;
constexpr int SS_META = SS_BARO + 3 * 8;
constexpr int SS_TOTAL = SS_META + METAS * 4;
constexpr int SA_WO = 0;
constexpr int SA_SLOT = SA_WO + HKV * 4 * 128 * 16;
constexpr int SA_ML = SA_SLOT + NSLOT * 1024;
constexpr int SA_QRED = SA_ML + 2 * NSLOT * 8;
constexpr int SA_O = SA_QRED + QLEAD * NAR * 8 * 256;
constexpr int ORED_N = (4 + 2 * DEF + 3) / 4 * 4;
constexpr int SA_ORED = SA_O + HKV * 512;
constexpr int SA_WT = SA_ORED + 16 * 36 * 4;
constexpr int SA_BAR = SA_WT + 4 * 32 * 4;
constexpr int SA_BARML = SA_BAR + 8;
constexpr int SA_BARDEF = SA_BARML + 8;
constexpr int SA_BARWO = SA_BARDEF + 8;
constexpr int SA_BARQ = SA_BARWO + 8;
constexpr int SA_BARO = SA_BARQ + QLEAD * 8;
constexpr int SA_NBAR = 4 + QLEAD + HKV - DEF;
constexpr int SA_TOTAL = SA_BAR + SA_NBAR * 8;
constexpr int SM_TOTAL = SS_TOTAL > SA_TOTAL ? SS_TOTAL : SA_TOTAL;

constexpr uint32_t SPIN_LIMIT = 1u << 22;

struct Scratch {
    uint4 part[HKV][MAX_CL][128];
    unsigned long long qpk[QCOLS / 2];
    unsigned int epoch;
    unsigned int pad0[31];
    unsigned int ticket;
    unsigned int pad1[31];
};
__device__ __align__(128) Scratch g_scratch;

#define TRACE(slot) do { } while (0)
#define PROG(t) do { } while (0)

__device__ __forceinline__ uint32_t smem_u32(const void* p) { return (uint32_t)__cvta_generic_to_shared(p); }
__device__ __forceinline__ uint32_t pin(uint32_t v) {
    asm volatile("mov.b32 %0, %0;" : "+r"(v));
    return v;
}
template <typename T>
__device__ __forceinline__ T* pin(T* p) {
    asm volatile("mov.b64 %0, %0;" : "+l"(p));
    return p;
}
__device__ __forceinline__ uint32_t mapa(uint32_t a, uint32_t rank) {
    uint32_t r;
    asm("mapa.shared::cluster.u32 %0, %1, %2;" : "=r"(r) : "r"(a), "r"(rank));
    return r;
}
__device__ __forceinline__ void mbar_init(uint32_t bar, uint32_t cnt) {
    asm volatile("mbarrier.init.shared::cta.b64 [%0], %1;" ::"r"(bar), "r"(cnt) : "memory");
}
__device__ __forceinline__ void mbar_expect_tx(uint32_t bar, uint32_t bytes) {
    asm volatile("mbarrier.arrive.expect_tx.shared::cta.b64 _, [%0], %1;" ::"r"(bar), "r"(bytes) : "memory");
}
__device__ __forceinline__ void mbar_arrive(uint32_t bar) {
    asm volatile("mbarrier.arrive.shared::cta.b64 _, [%0];" ::"r"(bar) : "memory");
}
__device__ __forceinline__ void mbar_arrive_remote(uint32_t cbar) {
    asm volatile("mbarrier.arrive.release.cluster.shared::cluster.b64 _, [%0];" ::"r"(cbar) : "memory");
}
__device__ __forceinline__ bool mbar_try_for(uint32_t bar, uint32_t parity, uint32_t ns) {
    uint32_t ok;
    asm volatile(
        "{\n.reg .pred p;\nmbarrier.try_wait.parity.shared::cta.b64 p, [%1], %2, %3;\nselp.u32 %0, 1, 0, p;\n}"
        : "=r"(ok) : "r"(bar), "r"(parity), "r"(ns) : "memory");
    return ok != 0;
}
__device__ __forceinline__ void mbar_wait(uint32_t bar, uint32_t parity) {
    uint32_t n = 0;
    while (!mbar_try_for(bar, parity, GQA_HINT)) {
        if (++n > SPIN_LIMIT) __trap();
    }
}
__device__ __forceinline__ void cluster_arrive_relaxed() { asm volatile("barrier.cluster.arrive.relaxed.aligned;" ::: "memory"); }
__device__ __forceinline__ void cluster_wait() { asm volatile("barrier.cluster.wait.acquire.aligned;" ::: "memory"); }
__device__ __forceinline__ void st_async_v4(uint32_t caddr, float a, float b, float c, float d, uint32_t cbar) {
    asm volatile("st.async.weak.shared::cluster.mbarrier::complete_tx::bytes.v4.f32 [%0], {%1,%2,%3,%4}, [%5];"
                 ::"r"(caddr), "f"(a), "f"(b), "f"(c), "f"(d), "r"(cbar) : "memory");
}
__device__ __forceinline__ void st_async_v2(uint32_t caddr, uint32_t a, uint32_t b, uint32_t cbar) {
    asm volatile("st.async.weak.shared::cluster.mbarrier::complete_tx::bytes.v2.b32 [%0], {%1,%2}, [%3];"
                 ::"r"(caddr), "r"(a), "r"(b), "r"(cbar) : "memory");
}
__device__ __forceinline__ void st_async_b32(uint32_t caddr, uint32_t a, uint32_t cbar) {
    asm volatile("st.async.weak.shared::cluster.mbarrier::complete_tx::bytes.b32 [%0], %1, [%2];"
                 ::"r"(caddr), "r"(a), "r"(cbar) : "memory");
}
__device__ __forceinline__ void bulk_load(uint32_t dst, const void* src, uint32_t bytes, uint32_t bar, uint64_t pol) {
    asm volatile(
        "cp.async.bulk.shared::cluster.global.mbarrier::complete_tx::bytes.L2::cache_hint [%0], [%1], %2, [%3], %4;"
        ::"r"(dst), "l"(src), "r"(bytes), "r"(bar), "l"(pol) : "memory");
}
__device__ __forceinline__ void l2_prefetch(const void* src, uint32_t bytes) {
    asm volatile("cp.async.bulk.prefetch.L2.global [%0], %1;" ::"l"(src), "r"(bytes) : "memory");
}
__device__ __forceinline__ void tma_load_2d(uint32_t dst, const CUtensorMap* tm, int c0, int c1, uint32_t bar) {
    asm volatile("cp.async.bulk.tensor.2d.shared::cluster.global.mbarrier::complete_tx::bytes [%0], [%1, {%3, %4}], [%2];"
                 ::"r"(dst), "l"(tm), "r"(bar), "r"(c0), "r"(c1) : "memory");
}
__device__ __forceinline__ uint4 lds128(uint32_t a) {
    uint4 v;
    asm volatile("ld.shared.v4.u32 {%0,%1,%2,%3}, [%4];" : "=r"(v.x), "=r"(v.y), "=r"(v.z), "=r"(v.w) : "r"(a) : "memory");
    return v;
}
__device__ __forceinline__ float4 lds128f(uint32_t a) {
    float4 v;
    asm volatile("ld.shared.v4.f32 {%0,%1,%2,%3}, [%4];" : "=f"(v.x), "=f"(v.y), "=f"(v.z), "=f"(v.w) : "r"(a) : "memory");
    return v;
}
__device__ __forceinline__ uint4 ldsm_x4_trans(uint32_t a) {
    uint4 v;
    asm volatile("ldmatrix.sync.aligned.m8n8.x4.trans.shared.b16 {%0,%1,%2,%3}, [%4];"
                 : "=r"(v.x), "=r"(v.y), "=r"(v.z), "=r"(v.w) : "r"(a) : "memory");
    return v;
}
__device__ __forceinline__ void mma_bf16(float (&c)[4], uint32_t a0, uint32_t a1, uint32_t a2, uint32_t a3,
                                         uint32_t b0, uint32_t b1) {
    asm volatile(
        "mma.sync.aligned.m16n8k16.row.col.f32.bf16.bf16.f32 {%0,%1,%2,%3}, {%4,%5,%6,%7}, {%8,%9}, {%0,%1,%2,%3};"
        : "+f"(c[0]), "+f"(c[1]), "+f"(c[2]), "+f"(c[3])
        : "r"(a0), "r"(a1), "r"(a2), "r"(a3), "r"(b0), "r"(b1));
}
__device__ __forceinline__ uint4 ldg_nc128(const void* p) {
    uint4 v;
    asm volatile("ld.global.nc.L1::no_allocate.L2::128B.v4.u32 {%0,%1,%2,%3}, [%4];"
                 : "=r"(v.x), "=r"(v.y), "=r"(v.z), "=r"(v.w) : "l"(p));
    return v;
}
__device__ __forceinline__ uint32_t ld_relaxed32(const void* p) {
    uint32_t v;
    asm volatile("ld.relaxed.gpu.global.b32 %0, [%1];" : "=r"(v) : "l"(p) : "memory");
    return v;
}
__device__ __forceinline__ void st_relaxed64(void* p, unsigned long long v) {
    asm volatile("st.relaxed.gpu.global.b64 [%0], %1;" ::"l"(p), "l"(v) : "memory");
}
__device__ __forceinline__ void ld_relaxed64x2(const void* p, unsigned long long& lo, unsigned long long& hi) {
    asm volatile("ld.relaxed.gpu.global.v2.b64 {%0, %1}, [%2];" : "=l"(lo), "=l"(hi) : "l"(p) : "memory");
}
__device__ __forceinline__ void ld_relaxed128(const void* p, unsigned long long& lo, unsigned long long& hi) {
    asm volatile("{\n.reg .b128 t;\nld.relaxed.gpu.global.b128 t, [%2];\nmov.b128 {%0, %1}, t;\n}"
                 : "=l"(lo), "=l"(hi) : "l"(p) : "memory");
}
__device__ __forceinline__ void st_relaxed128(void* p, unsigned long long lo, unsigned long long hi) {
    asm volatile("{\n.reg .b128 t;\nmov.b128 t, {%1, %2};\nst.relaxed.gpu.global.b128 [%0], t;\n}"
                 ::"l"(p), "l"(lo), "l"(hi) : "memory");
}
__device__ __forceinline__ float ex2(float x) {
    float y;
    asm("ex2.approx.ftz.f32 %0, %1;" : "=f"(y) : "f"(x));
    return y;
}
__device__ __forceinline__ float rcp(float x) {
    float y;
    asm("rcp.approx.ftz.f32 %0, %1;" : "=f"(y) : "f"(x));
    return y;
}
__device__ __forceinline__ float warp_max(float v) {
    int k = __float_as_int(v);
    k ^= (k >> 31) & 0x7fffffff;
    k = __reduce_max_sync(0xffffffffu, k);
    k ^= (k >> 31) & 0x7fffffff;
    return __int_as_float(k);
}
__device__ __forceinline__ uint32_t pack_bf16(float lo, float hi) {
    uint32_t r;
    asm("cvt.rn.bf16x2.f32 %0, %1, %2;" : "=r"(r) : "f"(hi), "f"(lo));
    return r;
}
__device__ __forceinline__ float bf_lo(uint32_t v) { return __uint_as_float(v << 16); }
__device__ __forceinline__ float bf_hi(uint32_t v) { return __uint_as_float(v & 0xffff0000u); }
__device__ __forceinline__ void named_sync(int id, int n) { asm volatile("bar.sync %0, %1;" ::"r"(id), "r"(n) : "memory"); }
__device__ __forceinline__ void fma8(float* a, float s, const uint4& w) {
    a[0] = fmaf(s, bf_lo(w.x), a[0]); a[1] = fmaf(s, bf_hi(w.x), a[1]);
    a[2] = fmaf(s, bf_lo(w.y), a[2]); a[3] = fmaf(s, bf_hi(w.y), a[3]);
    a[4] = fmaf(s, bf_lo(w.z), a[4]); a[5] = fmaf(s, bf_hi(w.z), a[5]);
    a[6] = fmaf(s, bf_lo(w.w), a[6]); a[7] = fmaf(s, bf_hi(w.w), a[7]);
}

__global__ void __cluster_dims__(CL, 1, 1) __launch_bounds__(NTHREADS, 1)
gqa_decode_kernel(int ncl, uint32_t zero, const __nv_bfloat16* __restrict__ kc, const __nv_bfloat16* __restrict__ vc,
                  const __nv_bfloat16* __restrict__ wq, const __nv_bfloat16* __restrict__ x, Scratch* __restrict__ sc,
                  const __nv_bfloat16* __restrict__ wo, __nv_bfloat16* __restrict__ out,
                  const __grid_constant__ CUtensorMap wo_map, const __grid_constant__ CUtensorMap wo_map48) {
    extern __shared__ __align__(1024) unsigned char smem[];
    const uint32_t sb = smem_u32(smem);
    const int tid = threadIdx.x, warp = tid >> 5, lane = tid & 31;
    const int rank = blockIdx.x % CL, cl = blockIdx.x / CL;
    constexpr float SCL = 0.08838834764831845f * 1.4426950408889634f;

    if (rank < NSR) {
        const uint32_t bar_full = sb + SS_BAR, bar_empty = bar_full + STAGES * 8;
        const uint32_t bar_q = bar_empty + STAGES * 8, bar_free = bar_q + HKV * 8, bar_fk = bar_free + NAR * 8;
        volatile uint32_t* meta = reinterpret_cast<volatile uint32_t*>(smem + SS_META);
        if (warp > NCONS + 1) return;
        if (warp == NCONS + 1) {
            const uint32_t tag = ld_relaxed32(&sc->epoch) + 1u;
            if (lane == 0) {
#pragma unroll
                for (int a = 0; a < NAR; a++) mbar_init(bar_free + a * 8, 1);
#pragma unroll
                for (int k = 0; k < DEFK; k++) mbar_init(sb + SS_BARO + k * 8, 1);
                asm volatile("fence.mbarrier_init.release.cluster;" ::: "memory");
            }
            __syncwarp();
            cluster_arrive_relaxed();
            if (lane == 0) {
#pragma unroll
                for (int h = 0; h < HKV; h++) mbar_init(bar_q + h * 8, 32);
#pragma unroll
                for (int k = 0; k < DEFK; k++) mbar_expect_tx(sb + SS_BARO + k * 8, 512);
                if (DEFK > 0) asm volatile("prefetch.tensormap [%0];" ::"l"(&wo_map48) : "memory");
            }
            __syncwarp();
            asm volatile("bar.arrive 1, %0;" ::"n"((NCONS + 2) * 32) : "memory");
#pragma unroll 1
            for (int h = 0; h < HKV; h++) {
                unsigned long long lo[2], hi[2];
                uint32_t n = 0;
                while (true) {
                    bool ok = true;
#pragma unroll
                    for (int k = 0; k < 2; k++) {
                        ld_relaxed64x2(&sc->qpk[h * 128 + (k * 32 + lane) * 2], lo[k], hi[k]);
                        ok = ok && ((uint32_t)(lo[k] >> 32) == tag) && ((uint32_t)(hi[k] >> 32) == tag);
                    }
                    if (ok) break;
                    if (h > 0) __nanosleep(500);
                    if (++n > SPIN_LIMIT) __trap();
                }
#pragma unroll
                for (int k = 0; k < 2; k++)
                    *reinterpret_cast<uint2*>(smem + SS_Q + h * 512 + (k * 32 + lane) * 8) = make_uint2((uint32_t)lo[k], (uint32_t)hi[k]);
                mbar_arrive(bar_q + h * 8);
            }
            return;
        }
        if (warp == NCONS) {
            const int ns = ncl * NSR, sid = cl * NSR + rank;
            uint64_t pol = 0;
            const char* kp = reinterpret_cast<const char*>(kc);
            const char* vp = reinterpret_cast<const char*>(vc);
            auto issue_k = [&](int i, int s, int t) {
                PROG(t);
                mbar_expect_tx(bar_fk + s * 8, TILE_BYTES);
                bulk_load(sb + SS_STAGE + s * STAGE_BYTES, kp + (size_t)t * TILE_BYTES, TILE_BYTES, bar_fk + s * 8, pol);
                meta[(i + 1) % METAS] = ((uint32_t)(i + 1) << 5) | (uint32_t)(t / TILES_PER_HEAD);
            };
            auto issue_v = [&](int s, int t) {
                mbar_expect_tx(bar_full + s * 8, TILE_BYTES);
                bulk_load(sb + SS_STAGE + s * STAGE_BYTES + TILE_BYTES, vp + (size_t)t * TILE_BYTES, TILE_BYTES, bar_full + s * 8, pol);
            };
            auto issue = [&](int i, int s, int t) { issue_k(i, s, t); issue_v(s, t); };
            if (lane == 0) TRACE(0);
            if (lane == 0) {
                l2_prefetch(kp + (size_t)sid * TILE_BYTES, TILE_BYTES);
                l2_prefetch(vp + (size_t)sid * TILE_BYTES, TILE_BYTES);
            }
            if (lane < METAS) meta[lane] = 0;
            __syncwarp();
            long long t_start = 0;
            if (lane == 0) {
#pragma unroll
                for (int s = 0; s < STAGES; s++) {
                    mbar_init(bar_full + s * 8, 1);
                    mbar_init(bar_fk + s * 8, 1);
                    mbar_init(bar_empty + s * 8, 2);
                }
                asm volatile("fence.proxy.async.shared::cta;" ::: "memory");
                asm volatile("createpolicy.fractional.L2::evict_first.b64 %0, 1.0;" : "=l"(pol));
                t_start = clock64();
#pragma unroll
                for (int s = 0; s < INIT; s++) issue(s, s, sid + s * ns);
                TRACE(1);
            }
            __syncwarp();
            asm volatile("bar.arrive 1, %0;" ::"n"((NCONS + 2) * 32) : "memory");
            cluster_arrive_relaxed();
            if (lane == 0) {
#pragma unroll 1
                for (int s = INIT; s < STAGES; s++) {
                    while (clock64() - t_start < (long long)(s - INIT + 1) * GQA_PACE) { }
                    issue(s, s, sid + s * ns);
                }
#pragma unroll 1
                for (int k = 0; k < GQA_PFN; k++) {
                    bool freed = false;
                    while (clock64() - t_start < (long long)(STAGES - INIT + 1 + k) * GQA_PACE && !freed)
                        freed = mbar_try_for(bar_empty, 0, 64);
                    if (freed) break;
                    l2_prefetch(kp + (size_t)(sid + (STAGES + k) * ns) * TILE_BYTES, TILE_BYTES);
                    l2_prefetch(vp + (size_t)(sid + (STAGES + k) * ns) * TILE_BYTES, TILE_BYTES);
                }
                TRACE(52);
                constexpr int NSTATIC = STAGES + (GQA_PFN > 1 ? GQA_PFN : 1);
                const int base = NSTATIC * ns;
                int tk = sid + STAGES * ns, tprev = -1;
                int i = STAGES;
                int s = 0, sv = STAGES - 1;
                uint32_t ph = 1;
                int sp = STAGES - INFL, spv = STAGES - INFL - 1;
                uint32_t php = 0, phv = 0;
                while (true) {
                    const int t = tk;
                    if (t < NTILES) {
                        mbar_wait(bar_empty + s * 8, ph ^ 1);
                        mbar_wait(bar_fk + sp * 8, php);
                        issue_k(i, s, t);
                        if (i < STAGES + 6) TRACE(53 + i - STAGES);
                        tk = (i + 1 < NSTATIC) ? t + ns : base + (int)atomicAdd(&sc->ticket, 1u);
                    } else {
#pragma unroll
                        for (int k = 0; k < NPAIR; k++) meta[(i + 1 + k) % METAS] = ((uint32_t)(i + 1 + k) << 5) | (uint32_t)(HKV + k);
                    }
                    if (tprev >= 0) {
                        if (t < NTILES || GQA_LIFT == 0) mbar_wait(bar_full + spv * 8, phv);
                        issue_v(sv, tprev);
                    }
                    if (t >= NTILES) {
                        if (DEFK > 0 && cl < NOWN / NAR) {
#pragma unroll
                            for (int k = 0; k < GQA_TRIGW; k++) {
                                mbar_wait(bar_full + sp * 8, php);
                                if (++sp == STAGES) { sp = 0; php ^= 1; }
                            }
                            TRACE(14);
#pragma unroll 1
                            for (int k = 0; k < DEFK; k++) {
                                mbar_wait(bar_empty + s * 8, ph ^ 1);
                                mbar_expect_tx(bar_fk + s * 8, 256 * 96);
                                tma_load_2d(sb + SS_STAGE + s * STAGE_BYTES, &wo_map48, cl * 48, (k * NSR + rank) * 256, bar_fk + s * 8);
                                if (++s == STAGES) { s = 0; ph ^= 1; }
                            }
                        }
                        break;
                    }
                    tprev = t;
                    sv = s;
                    spv = sp;
                    phv = php;
                    i++;
                    if (++s == STAGES) { s = 0; ph ^= 1; }
                    if (++sp == STAGES) { sp = 0; php ^= 1; }
                }
            }
            return;
        }
        cluster_arrive_relaxed();
        const int g = lane >> 2, t4 = lane & 3;
        const uint32_t koff = ((warp & 1) * 32 + g) * 256 + t4 * 16 + (g & 1) * 64;
        const uint32_t qoff = (g >> 2) * 256 + t4 * 16 + (((g >> 1) ^ g) & 1) * 64;
        const int kk = lane & 7, mi = lane >> 3;
        const uint32_t voff = TILE_BYTES + ((warp & 1) * 32 + 2 * (kk >> 1) + (mi >> 1) + 8 * (kk & 1)) * 256 +
                              ((mi ^ kk) & 1) * 16 + (kk >> 1) * 32;
        const int slot = rank * NCONS + warp;
        const uint32_t ka0 = pin(sb + SS_STAGE + koff), ka1 = pin(sb + SS_STAGE + (koff ^ 64));
        const uint32_t va0 = pin(sb + SS_STAGE + voff), va1 = pin(sb + SS_STAGE + (voff ^ 32));
        const uint32_t va2 = pin(sb + SS_STAGE + (voff ^ 64)), va3 = pin(sb + SS_STAGE + (voff ^ 96));
        const uint32_t bars = pin(bar_full), metas = pin(sb + SS_META);
        const uint32_t src0 = pin(8 * t4 + 2 * (g >> 2));
        const uint32_t bmask = pin(t4 == (g & 3) ? 0xffffffffu : 0u);
        const uint32_t oddm = pin((g ^ t4) & 1);
        const uint32_t zr = pin(zero), ln = pin(lane);
        const uint32_t poff = pin(SA_SLOT + slot * 1024 + (t4 >> 1) * 512 + (g * 2 + (t4 & 1)) * 16);
        const uint32_t mloff = pin((g == 0 && (t4 & 1) == 0) ? SA_ML + ((t4 >> 1) * NSLOT + slot) * 8 : 0);
        named_sync(1, (NCONS + 2) * 32);

        constexpr uint32_t FK = (2 * STAGES + HKV + NAR) * 8, EM = STAGES * 8;
        static_assert(STAGES % NPAIR == 0 && NSLOT <= 32, "a warp pair owns every NPAIR-th stage");
        int s = warp >> 1;
        uint32_t ph = 0, seq = 1 + (warp >> 1);
        int th = 0;
#pragma unroll 1
        for (int h = 0; h < HKV; h++) {
            mbar_wait(bar_q + h * 8, 0);
            if (h == 0 && tid == 0) TRACE(3);
            uint4 qf[4];
#pragma unroll
            for (int j = 0; j < 4; j++) qf[j] = lds128(sb + SS_Q + h * 512 + (qoff ^ (j * 64)));
            float acc[8][4];
#pragma unroll
            for (int i = 0; i < 8; i++) { acc[i][0] = acc[i][1] = acc[i][2] = acc[i][3] = 0.f; }
            float m = -INFINITY, l = 0.f, lsum = 0.f;
            bool ml_sent = false;
            if (h == 0) cluster_wait();
            if (h >= NAR) mbar_wait(bar_free + (h % NAR) * 8, (uint32_t)(h / NAR - 1) & 1u);
            const uint32_t rb_ = pin(mapa(sb, NSR + h % NAR));
            while (th == h) {
                const uint32_t so = s * STAGE_BYTES, bv = bars + s * 8, pvh = ph;
                float sc[4];
                {
                    const uint32_t a0 = ka0 + so, a1 = ka1 + so;
                    mbar_wait(bv + FK, pvh);
#pragma unroll
                    for (int u = 0; u < 2; u++) {
                        uint4 ra[4], rb[4];
                        ra[0] = lds128(a0 + u * 4096); rb[0] = lds128(a0 + u * 4096 + 2048);
                        ra[1] = lds128(a1 + u * 4096); rb[1] = lds128(a1 + u * 4096 + 2048);
                        ra[2] = lds128(a0 + u * 4096 + 128); rb[2] = lds128(a0 + u * 4096 + 2048 + 128);
                        ra[3] = lds128(a1 + u * 4096 + 128); rb[3] = lds128(a1 + u * 4096 + 2048 + 128);
                        float c0[4] = {0.f, 0.f, 0.f, 0.f}, c1[4] = {0.f, 0.f, 0.f, 0.f};
#pragma unroll
                        for (int j = 0; j < 4; j++) {
                            mma_bf16(c0, ra[j].x, rb[j].x, ra[j].y, rb[j].y, qf[j].x, qf[j].y);
                            mma_bf16(c1, ra[j].z, rb[j].z, ra[j].w, rb[j].w, qf[j].z, qf[j].w);
                        }
                        sc[2 * u] = oddm ? (c0[1] + c1[1]) : (c0[0] + c1[0]);
                        sc[2 * u + 1] = oddm ? (c0[3] + c1[3]) : (c0[2] + c1[2]);
                    }
                }
                float mx = fmaxf(fmaxf(sc[0], sc[1]), fmaxf(sc[2], sc[3]));
                mx = fmaxf(mx, __shfl_xor_sync(0xffffffffu, mx, 4));
                mx = fmaxf(mx, __shfl_xor_sync(0xffffffffu, mx, 8));
                mx = fmaxf(mx, __shfl_xor_sync(0xffffffffu, mx, 16));
                const float mn = fmaxf(m, mx);
                const float alpha = ex2((m - mn) * SCL);
                const float p0 = ex2((sc[0] - mn) * SCL), p1 = ex2((sc[1] - mn) * SCL);
                const float p2 = ex2((sc[2] - mn) * SCL), p3 = ex2((sc[3] - mn) * SCL);
                m = mn;
                l = fmaf(l, alpha, (p0 + p1) + (p2 + p3));
                const uint32_t pka = pack_bf16(p0, p1), pkb = pack_bf16(p2, p3);
                uint32_t bf[4];
                bf[0] = __shfl_sync(0xffffffffu, pka, src0) & bmask;
                bf[1] = __shfl_sync(0xffffffffu, pka, src0 + 4) & bmask;
                bf[2] = __shfl_sync(0xffffffffu, pkb, src0) & bmask;
                bf[3] = __shfl_sync(0xffffffffu, pkb, src0 + 4) & bmask;
#pragma unroll
                for (int i = 0; i < 8; i++) { acc[i][0] *= alpha; acc[i][1] *= alpha; acc[i][2] *= alpha; acc[i][3] *= alpha; }
                lsum = l + __shfl_xor_sync(0xffffffffu, l, 4);
                lsum += __shfl_xor_sync(0xffffffffu, lsum, 8);
                lsum += __shfl_xor_sync(0xffffffffu, lsum, 16);
                s += NPAIR;
                if (s >= STAGES) { s -= STAGES; ph ^= 1; }
                seq += NPAIR;
                const uint32_t a0 = va0 + so, a1 = va1 + so, a2 = va2 + so, a3 = va3 + so, ma = metas + (seq % METAS) * 4;
                uint32_t mt, dep = 0, n = 0;
                while (true) {
                    asm volatile("ld.volatile.shared.u32 %0, [%1];" : "=r"(mt) : "r"(ma) : "memory");
                    if ((mt >> 5) == seq) {
                        if ((int)(mt & 31u) != h) {
                            if (mloff) st_async_v2(rb_ + mloff, __float_as_uint(m), __float_as_uint(lsum), rb_ + SA_BARML);
                            ml_sent = true;
                        }
                        mbar_wait(bv, pvh);
                        break;
                    }
                    if (mbar_try_for(bv, pvh, 128)) break;
                    if (++n > SPIN_LIMIT) __trap();
                }
                __syncwarp();
#pragma unroll
                for (int u = 0; u < 2; u++) {
                    uint4 va[8];
                    va[0] = ldsm_x4_trans(a0 + u * 4096); va[1] = ldsm_x4_trans(a1 + u * 4096);
                    va[2] = ldsm_x4_trans(a2 + u * 4096); va[3] = ldsm_x4_trans(a3 + u * 4096);
                    va[4] = ldsm_x4_trans(a0 + u * 4096 + 128); va[5] = ldsm_x4_trans(a1 + u * 4096 + 128);
                    va[6] = ldsm_x4_trans(a2 + u * 4096 + 128); va[7] = ldsm_x4_trans(a3 + u * 4096 + 128);
#pragma unroll
                    for (int i = 0; i < 8; i++)
                        mma_bf16(acc[i], __byte_perm(va[i].x, va[i].y, 0x7610), __byte_perm(va[i].y, va[i].x, 0x7610),
                                 __byte_perm(va[i].z, va[i].w, 0x7610), __byte_perm(va[i].w, va[i].z, 0x7610),
                                 bf[2 * u], bf[2 * u + 1]);
                    dep |= (va[0].x | va[1].x) | (va[2].x | va[3].x | va[4].x) | (va[5].x | va[6].x | va[7].x);
                }
                if (ln == 0) mbar_arrive(bv + EM + (dep & zr));
                n = 0;
                while ((mt >> 5) != seq) {
                    if (n) __nanosleep(32);
                    asm volatile("ld.volatile.shared.u32 %0, [%1];" : "=r"(mt) : "r"(ma) : "memory");
                    if (++n > SPIN_LIMIT) __trap();
                }
                th = (int)(mt & 31u);
            }
            if (!ml_sent && mloff) st_async_v2(rb_ + mloff, __float_as_uint(m), __float_as_uint(lsum), rb_ + SA_BARML);
            float w[8];
#pragma unroll
            for (int k = 0; k < 4; k++) {
                const int i = (k & 1) | ((k & 2) << 1);
                w[2 * k] = (acc[i][0] + acc[i ^ 1][1]) + __shfl_xor_sync(0xffffffffu, acc[i ^ 2][0] + acc[i ^ 3][1], 1);
                w[2 * k + 1] = (acc[i][2] + acc[i ^ 1][3]) + __shfl_xor_sync(0xffffffffu, acc[i ^ 2][2] + acc[i ^ 3][3], 1);
            }
            st_async_v4(rb_ + poff, w[0], w[1], w[2], w[3], rb_ + SA_BAR);
            st_async_v4(rb_ + poff + 256, w[4], w[5], w[6], w[7], rb_ + SA_BAR);
            if (tid == 0) TRACE(16 + h);
        }
        if (DEFK > 0 && cl < NOWN / NAR && th - HKV < DEFK) {
            const int k = th - HKV;
            const uint32_t ab = sb + SS_STAGE + s * STAGE_BYTES +
                                ((warp & 1) * 128 + (lane >> 4) * 16 + ((lane >> 1) & 3) + (lane & 1) * 8) * 96 + ((lane >> 3) & 1) * 16;
            uint4 bo[4];
            mbar_wait(sb + SS_BARO + k * 8, 0);
#pragma unroll
            for (int i = 0; i < 4; i++) bo[i] = lds128(sb + SS_O + k * 512 + ((warp & 1) * 64 + i * 16 + t4 * 4) * 4);
            float d[3][2][4];
#pragma unroll
            for (int a = 0; a < 3; a++)
#pragma unroll
                for (int c = 0; c < 2; c++) d[a][c][0] = d[a][c][1] = d[a][c][2] = d[a][c][3] = 0.f;
            const uint32_t dsto = SA_ORED + (g * ORED_N + 4 + (k * NSR + rank) * 2 + (warp & 1)) * 4;
            mbar_wait(bars + FK + s * 8, ph);
#pragma unroll
            for (int i = 0; i < 4; i++) {
#pragma unroll
                for (int c = 0; c < 2; c++) {
#pragma unroll
                    for (int a = 0; a < 3; a++) {
                        const uint4 wf = ldsm_x4_trans(ab + ((i >> 1) * 64 + c * 32 + (i & 1) * 4) * 96 + a * 32);
                        mma_bf16(d[a][c], wf.x, wf.y, wf.z, wf.w, c ? bo[i].z : bo[i].x, c ? bo[i].w : bo[i].y);
                    }
                }
            }
            if (t4 == 0) {
#pragma unroll
                for (int a = 0; a < 3; a++) {
                    const uint32_t ra_ = mapa(sb, NSR + a);
                    st_async_b32(ra_ + dsto, __float_as_uint(d[a][0][0] + d[a][1][0]), ra_ + SA_BARDEF);
                    st_async_b32(ra_ + dsto + 8 * ORED_N * 4, __float_as_uint(d[a][0][2] + d[a][1][2]), ra_ + SA_BARDEF);
                }
            }
            if (lane == 0) TRACE(15);
        }
        return;
    }

    const int ar = rank - NSR, aid = cl * NAR + ar;
    const uint32_t bar_merge = sb + SA_BAR, bar_qred = sb + SA_BARQ, bar_o = sb + SA_BARO - DEF * 8;
    if (tid == 0) TRACE(4);
    const uint32_t tag = ld_relaxed32(&sc->epoch) + 1u;
    {
        const int row0 = ar * QROWS + (tid >> 3);
        const __nv_bfloat16* wp = wq + (size_t)row0 * QCOLS + (tid & 7) * 8;
        uint4 w[6];
#pragma unroll
        for (int i = 0; i < 6; i++) w[i] = ldg_nc128(wp + cl * 64 + (size_t)i * 32 * QCOLS);
        float xv[6];
#pragma unroll
        for (int i = 0; i < 6; i++) xv[i] = __bfloat162float(x[row0 + i * 32]);
        if (lane == 0) {
            mbar_init(bar_merge + warp * 8, 1);
            if (warp + 8 < SA_NBAR) mbar_init(bar_merge + (warp + 8) * 8, 1);
            if (warp + 16 < SA_NBAR) mbar_init(bar_merge + (warp + 16) * 8, 1);
            asm volatile("fence.mbarrier_init.release.cluster;" ::: "memory");
        }
        __syncwarp();
        cluster_arrive_relaxed();
        if (lane == 0) {
            const uint32_t bytes = warp == 0 ? MERGE_BYTES : warp == 1 ? ML_BYTES : warp == 2 ? DEF * 2 * 64
                                 : warp == 3 ? (HKV - DEF) * 256 * 32 : warp < 4 + QLEAD ? NAR * 8 * 256 : 512;
            mbar_expect_tx(bar_merge + warp * 8, bytes);
            if (warp + 8 < SA_NBAR) mbar_expect_tx(bar_merge + (warp + 8) * 8, 512);
            if (warp + 16 < SA_NBAR) mbar_expect_tx(bar_merge + (warp + 16) * 8, 512);
        }
        __syncwarp();
        cluster_wait();
        int rnd = 0;
#pragma unroll 1
        for (int c = cl; c < NQITEM; c += ncl, rnd++) {
            if (rnd > 0) {
#pragma unroll
                for (int i = 0; i < 6; i++) w[i] = ldg_nc128(wp + c * 64 + (size_t)i * 32 * QCOLS);
            }
            float a[8];
#pragma unroll
            for (int k = 0; k < 8; k++) a[k] = 0.f;
#pragma unroll
            for (int i = 0; i < 6; i++) fma8(a, xv[i], w[i]);
            const bool u4 = lane & 16, u3 = lane & 8;
            float r4[4], r2[2];
#pragma unroll
            for (int k = 0; k < 4; k++)
                r4[k] = (u4 ? a[k + 4] : a[k]) + __shfl_xor_sync(0xffffffffu, u4 ? a[k] : a[k + 4], 16);
#pragma unroll
            for (int k = 0; k < 2; k++)
                r2[k] = (u3 ? r4[k + 2] : r4[k]) + __shfl_xor_sync(0xffffffffu, u3 ? r4[k] : r4[k + 2], 8);
            const int lead = rnd % NAR, lk = rnd / NAR;
            const uint32_t rb_ = mapa(sb, NSR + lead) + (tag & zero);
            st_async_v2(rb_ + SA_QRED + lk * (NAR * 8 * 256) + (ar * 8 + warp) * 256 + ((lane & 7) * 4 + (lane >> 3)) * 8,
                        __float_as_uint(r2[0]), __float_as_uint(r2[1]), rb_ + SA_BARQ + lk * 8);
            if (lead == ar) {
                if (warp == 0) {
                    mbar_wait(bar_qred + lk * 8, 0);
                    float s0 = 0.f, s1 = 0.f;
#pragma unroll
                    for (int k = 0; k < NAR * 8; k++) {
                        const float2 v = *reinterpret_cast<const float2*>(smem + SA_QRED + lk * (NAR * 8 * 256) + k * 256 + lane * 8);
                        s0 += v.x; s1 += v.y;
                    }
                    st_relaxed64(&sc->qpk[c * 32 + lane], (unsigned long long)pack_bf16(s0, s1) | ((unsigned long long)tag << 32));
                    if (rnd == 0 && lane == 0) TRACE(2);
                }
                named_sync(1, 256);
            }
            if (rnd == 0) {
                __nanosleep(GQA_D1);
                if (warp == 1) {
                    for (int r = aid + lane * ncl * NAR; r < D_MODEL; r += ncl * NAR * 32)
                        l2_prefetch(wq + (size_t)r * QCOLS + ncl * 64, (QCOLS - ncl * 64) * 2);
                    for (int r = DEF * NOWN + aid + lane * ncl * NAR; r < D_MODEL; r += ncl * NAR * 32)
                        l2_prefetch(wo + (size_t)r * QCOLS, QCOLS * 2);
                }
                __nanosleep(GQA_D2);
            }
        }
    }
    const int j = tid & 127, ow = warp & 3;
    const uint32_t aoff = sb + SA_WO + ((ow >> 1) * 128 + (ow & 1) * 64 + (lane >> 4) * 16 + ((lane >> 1) & 3) + (lane & 1) * 8) * 32 +
                          ((lane >> 3) & 1) * 16;
    const uint32_t boff = sb + SA_O + (ow * 32 + (lane & 3) * 4) * 4;
    float pacc[4][4];
#pragma unroll
    for (int i = 0; i < 4; i++) { pacc[i][0] = pacc[i][1] = pacc[i][2] = pacc[i][3] = 0.f; }
    auto load_w = [&](int h, uint4 (&wf)[4]) {
        mbar_wait(sb + SA_BARWO, 0);
#pragma unroll
        for (int i = 0; i < 4; i++) wf[i] = ldsm_x4_trans(aoff + h * 8192 + (i & 1) * 1024 + (i >> 1) * 128);
    };
    auto project = [&](int h, const uint4 (&wf)[4]) {
        const uint4 b0 = lds128(boff + h * 512), b1 = lds128(boff + h * 512 + 64);
        mma_bf16(pacc[0], wf[0].x, wf[0].y, wf[0].z, wf[0].w, b0.x, b0.y);
        mma_bf16(pacc[1], wf[1].x, wf[1].y, wf[1].z, wf[1].w, b0.z, b0.w);
        mma_bf16(pacc[2], wf[2].x, wf[2].y, wf[2].z, wf[2].w, b1.x, b1.y);
        mma_bf16(pacc[3], wf[3].x, wf[3].y, wf[3].z, wf[3].w, b1.z, b1.w);
    };
    if (warp < 4) {
        float* wbuf = reinterpret_cast<float*>(smem + SA_WT) + warp * 32;
        const uint32_t wb_addr = sb + SA_WT + warp * 128;
        uint4* dst = &sc->part[ar][cl][j];
        uint32_t ph = 0;
#pragma unroll 1
        for (int h = ar; h < HKV; h += NAR, dst += NAR * MAX_CL * 128) {
            mbar_wait(sb + SA_BARML, ph);
            float2 e = make_float2(-INFINITY, 0.f);
            if (lane < NSLOT) e = *reinterpret_cast<const float2*>(smem + SA_ML + ((warp >> 1) * NSLOT + lane) * 8);
            float M = warp_max(e.x);
            const bool none = (M == -INFINITY);
            if (none) M = 0.f;
            const float wt = ex2((e.x - M) * SCL);
            float L = wt * e.y;
#pragma unroll
            for (int o = 16; o > 0; o >>= 1) L += __shfl_xor_sync(0xffffffffu, L, o);
            const float lse = none ? -INFINITY : fmaf(M, SCL, __log2f(L));
            wbuf[lane] = none ? 0.f : wt * rcp(L);
            __syncwarp();
            float wk[(NSLOT + 3) / 4 * 4];
#pragma unroll
            for (int k = 0; k < (NSLOT + 3) / 4; k++) {
                const float4 w4 = lds128f(wb_addr + k * 16);
                wk[4 * k] = w4.x; wk[4 * k + 1] = w4.y; wk[4 * k + 2] = w4.z; wk[4 * k + 3] = w4.w;
            }
            mbar_wait(bar_merge, ph);
            ph ^= 1;
            float2 u[NSLOT];
#pragma unroll
            for (int k = 0; k < NSLOT; k++) u[k] = *reinterpret_cast<const float2*>(smem + SA_SLOT + k * 1024 + j * 8);
            float o0 = 0.f, o1 = 0.f, p0 = 0.f, p1 = 0.f;
#pragma unroll
            for (int k = 0; k < NSLOT; k += 2) {
                o0 = fmaf(wk[k], u[k].x, o0);         o1 = fmaf(wk[k], u[k].y, o1);
                p0 = fmaf(wk[k + 1], u[k + 1].x, p0); p1 = fmaf(wk[k + 1], u[k + 1].y, p1);
            }
            st_relaxed128(dst, (unsigned long long)__float_as_uint(lse) | ((unsigned long long)__float_as_uint(o0 + p0) << 32),
                          (unsigned long long)__float_as_uint(o1 + p1) | ((unsigned long long)tag << 32));
            if (tid == 0) TRACE(32 + h);
            if (h + NAR < HKV) {
                named_sync(2, 128);
                if (tid == 0) {
                    mbar_expect_tx(bar_merge, MERGE_BYTES);
                    mbar_expect_tx(sb + SA_BARML, ML_BYTES);
                }
                __syncwarp();
                if (tid < NSR) mbar_arrive_remote(mapa(sb + SS_BAR + (2 * STAGES + HKV + ar) * 8, tid));
            }
        }
    } else if (aid < NOWN) {
        if (j == 0) {
            asm volatile("fence.proxy.async.shared::cta;" ::: "memory");
#pragma unroll 1
            for (int h = DEF; h < HKV; h++) tma_load_2d(sb + SA_WO + h * 8192, &wo_map, aid * 16, h * 256, sb + SA_BARWO);
        }
        __syncwarp();
        const int par = lane & 1;
        const int pj = (ar == 0 ? 0 : 2 + 42 * ar) + ow * 11 + (lane >> 1);
        const bool comb = lane < 22 && pj < (ar == 2 ? 128 : 44 + 42 * ar);
        const uint32_t cmask = __ballot_sync(0xffffffffu, comb);
        const bool has6 = 12 + par < ncl, has7 = 14 + par < ncl;
        const uint4* src = &sc->part[0][par][comb ? pj : 0];
        const int off6 = has6 ? 6 * 256 : 0, off7 = has7 ? 7 * 256 : 0;
        const uint32_t oaddr = SA_O + pj * 4;
        const uint32_t r0 = pin(mapa(sb, NSR + par)), r2 = pin(mapa(sb, NSR + 2));
        float late = 0.f;
        const uint32_t sum_st = pin((lane & 3) == 0 ? sb + SA_ORED + ((lane >> 2) * ORED_N + ow) * 4 : 0u);
        const uint32_t sum_ld = pin(j < 16 ? sb + SA_ORED + j * ORED_N * 4 : 0u);
        __nv_bfloat16* const outp = pin(out + aid * 16 + j);
#pragma unroll 1
        for (int h = 0; h < HKV; h++, src += MAX_CL * 128) {
            uint4 wf[4];
            if (h >= DEF) load_w(h, wf);
            if (comb) {
                uint32_t d0 = r0 + oaddr + h * 512, e0 = r0 + SA_BARO + (h - DEF) * 8;
                uint32_t d2 = r2 + oaddr + h * 512, e2 = r2 + SA_BARO + (h - DEF) * 8;
                if (h < DEF) {
                    const uint32_t rs = mapa(sb, h % NSR);
                    d2 = rs + SS_O + (h / NSR) * 512 + pj * 4;
                    e2 = rs + SS_BARO + (h / NSR) * 8;
                    d0 = 0;
                }
                if (par) d2 = 0;
                d0 = pin(d0); e0 = pin(e0); d2 = pin(d2); e2 = pin(e2);
                unsigned long long lo[8], hi[8];
                uint32_t n = 0;
                while (true) {
#pragma unroll
                    for (int k = 0; k < 6; k++) ld_relaxed128(src + k * 256, lo[k], hi[k]);
                    ld_relaxed128(src + off6, lo[6], hi[6]);
                    ld_relaxed128(src + off7, lo[7], hi[7]);
                    uint32_t bad = 0;
#pragma unroll
                    for (int k = 0; k < 8; k++) bad |= (uint32_t)(hi[k] >> 32) ^ tag;
                    if (__all_sync(cmask, bad == 0)) break;
                    if (h < HKV - 1) __nanosleep(500);
                    if (++n > SPIN_LIMIT) __trap();
                }
                if (lane == 0 && warp < 6) TRACE(4 + warp);
                float e[8];
#pragma unroll
                for (int k = 0; k < 8; k++) e[k] = __uint_as_float((uint32_t)lo[k]);
                if (!has6) e[6] = -INFINITY;
                if (!has7) e[7] = -INFINITY;
                float mx = fmaxf(fmaxf(fmaxf(e[0], e[1]), fmaxf(e[2], e[3])), fmaxf(fmaxf(e[4], e[5]), fmaxf(e[6], e[7])));
                mx = fmaxf(mx, __shfl_xor_sync(cmask, mx, 1));
                float W = 0.f, o0 = 0.f, o1 = 0.f, W2 = 0.f, p0 = 0.f, p1 = 0.f;
#pragma unroll
                for (int k = 0; k < 8; k += 2) {
                    const float wa = ex2(e[k] - mx), wb = ex2(e[k + 1] - mx);
                    W += wa;
                    o0 = fmaf(wa, __uint_as_float((uint32_t)(lo[k] >> 32)), o0);
                    o1 = fmaf(wa, __uint_as_float((uint32_t)hi[k]), o1);
                    W2 += wb;
                    p0 = fmaf(wb, __uint_as_float((uint32_t)(lo[k + 1] >> 32)), p0);
                    p1 = fmaf(wb, __uint_as_float((uint32_t)hi[k + 1]), p1);
                }
                W += W2; o0 += p0; o1 += p1;
                W += __shfl_xor_sync(cmask, W, 1);
                o0 += __shfl_xor_sync(cmask, o0, 1);
                o1 += __shfl_xor_sync(cmask, o1, 1);
                const float inv = rcp(W);
                const uint32_t ob = pack_bf16(o0 * inv, o1 * inv);
                if (d0) st_async_b32(d0, ob, e0);
                if (d2) st_async_b32(d2, ob, e2);
            }
            __syncwarp();
            if (DEF > 0 && h == HKV - 1 && sum_ld) {
                mbar_wait(sb + SA_BARDEF, 0);
                float4 t = make_float4(0.f, 0.f, 0.f, 0.f);
#pragma unroll
                for (int k = 0; k < DEF / 2; k++) {
                    const float4 v = lds128f(sum_ld + 16 + k * 16);
                    t.x += v.x; t.y += v.y; t.z += v.z; t.w += v.w;
                }
                if (DEF & 1) {
                    const float2 v = *reinterpret_cast<const float2*>(smem + (sum_ld - sb) + 16 + (DEF / 2) * 16);
                    t.x += v.x; t.y += v.y;
                }
                late = (t.x + t.y) + (t.z + t.w);
            }
            __syncwarp();
            if (h >= DEF) {
                mbar_wait(bar_o + h * 8, 0);
                project(h, wf);
            }
        }
        if (sum_st) {
            asm volatile("st.shared.f32 [%0], %1;" ::"r"(sum_st), "f"((pacc[0][0] + pacc[1][0]) + (pacc[2][0] + pacc[3][0])) : "memory");
            asm volatile("st.shared.f32 [%0], %1;" ::"r"(sum_st + 8 * ORED_N * 4), "f"((pacc[0][2] + pacc[1][2]) + (pacc[2][2] + pacc[3][2])) : "memory");
        }
        named_sync(3, 128);
        if (sum_ld) {
            const float4 v = lds128f(sum_ld);
            const unsigned short r = __bfloat16_as_ushort(__float2bfloat16(((v.x + v.y) + (v.z + v.w)) + late));
            asm volatile("st.global.b16 [%0], %1;" ::"l"(outp), "h"(r) : "memory");
        }
        if (j == 0) TRACE(63);
        if (aid == 0 && j == 0) {
            *reinterpret_cast<volatile unsigned int*>(&sc->epoch) = tag;
            *reinterpret_cast<volatile unsigned int*>(&sc->ticket) = 0u;
        }
    }
}

constexpr int FB_SPLIT = 64;
__device__ float fb_q[QCOLS];
__device__ float fb_part[HQ][FB_SPLIT][DH + 2];
__device__ float fb_o[QCOLS];

__global__ void fb_q_kernel(const __nv_bfloat16* __restrict__ x, const __nv_bfloat16* __restrict__ wq) {
    const int c = blockIdx.x * blockDim.x + threadIdx.x;
    float a = 0.f;
    for (int i = 0; i < D_MODEL; i++) a = fmaf(__bfloat162float(x[i]), __bfloat162float(wq[(size_t)i * QCOLS + c]), a);
    fb_q[c] = __bfloat162float(__float2bfloat16(a));
}
__global__ void fb_attn_kernel(const __nv_bfloat16* __restrict__ kc, const __nv_bfloat16* __restrict__ vc) {
    const int sp = blockIdx.x, hq = blockIdx.y * 2 + (threadIdx.x >> 5), lane = threadIdx.x & 31;
    const size_t base = ((size_t)blockIdx.y * SK + (size_t)sp * (SK / FB_SPLIT)) * DH + lane * 4;
    const float4 q = *reinterpret_cast<const float4*>(&fb_q[hq * DH + lane * 4]);
    float m = -INFINITY, l = 0.f, a0 = 0.f, a1 = 0.f, a2 = 0.f, a3 = 0.f;
    for (int k = 0; k < SK / FB_SPLIT; k++) {
        const uint2 kv = *reinterpret_cast<const uint2*>(kc + base + (size_t)k * DH);
        const uint2 vv = *reinterpret_cast<const uint2*>(vc + base + (size_t)k * DH);
        float s = q.x * bf_lo(kv.x) + q.y * bf_hi(kv.x) + q.z * bf_lo(kv.y) + q.w * bf_hi(kv.y);
        for (int o = 16; o > 0; o >>= 1) s += __shfl_xor_sync(0xffffffffu, s, o);
        s *= 0.08838834764831845f;
        const float mn = fmaxf(m, s), al = __expf(m - mn), pw = __expf(s - mn);
        m = mn;
        l = l * al + pw;
        a0 = a0 * al + pw * bf_lo(vv.x); a1 = a1 * al + pw * bf_hi(vv.x);
        a2 = a2 * al + pw * bf_lo(vv.y); a3 = a3 * al + pw * bf_hi(vv.y);
    }
    float* dst = fb_part[hq][sp];
    dst[lane * 4] = a0; dst[lane * 4 + 1] = a1; dst[lane * 4 + 2] = a2; dst[lane * 4 + 3] = a3;
    if (lane == 0) { dst[DH] = m; dst[DH + 1] = l; }
}
__global__ void fb_combine_kernel() {
    const int hq = blockIdx.x, d = threadIdx.x;
    float M = -INFINITY, L = 0.f, a = 0.f;
    for (int s = 0; s < FB_SPLIT; s++) M = fmaxf(M, fb_part[hq][s][DH]);
    for (int s = 0; s < FB_SPLIT; s++) {
        const float w = __expf(fb_part[hq][s][DH] - M);
        L += w * fb_part[hq][s][DH + 1];
        a += w * fb_part[hq][s][d];
    }
    fb_o[hq * DH + d] = __bfloat162float(__float2bfloat16(a / L));
}
__global__ void fb_out_kernel(const __nv_bfloat16* __restrict__ wo, __nv_bfloat16* __restrict__ out) {
    const int c = blockIdx.x * blockDim.x + threadIdx.x;
    float a = 0.f;
    for (int i = 0; i < QCOLS; i++) a = fmaf(fb_o[i], __bfloat162float(wo[(size_t)i * D_MODEL + c]), a);
    out[c] = __float2bfloat16(a);
}

}

extern "C" void kernel_launch(void* const* d_in, const int* in_sizes, int n_in, void* d_out, int out_size) {
    (void)in_sizes; (void)n_in; (void)out_size;
    const __nv_bfloat16* x = (const __nv_bfloat16*)d_in[0];
    const __nv_bfloat16* kc = (const __nv_bfloat16*)d_in[1];
    const __nv_bfloat16* vc = (const __nv_bfloat16*)d_in[2];
    const __nv_bfloat16* wq = (const __nv_bfloat16*)d_in[3];
    const __nv_bfloat16* wo = (const __nv_bfloat16*)d_in[4];
    __nv_bfloat16* out = (__nv_bfloat16*)d_out;
    cudaStream_t stream = cudaStreamPerThread;

    cudaLaunchConfig_t cfg = {};
    cudaLaunchAttribute at[1];
    at[0].id = cudaLaunchAttributeClusterDimension;
    at[0].val.clusterDim.x = CL;
    at[0].val.clusterDim.y = 1;
    at[0].val.clusterDim.z = 1;
    cfg.attrs = at;
    cfg.numAttrs = 1;
    cfg.blockDim = dim3(NTHREADS);
    cfg.dynamicSmemBytes = SM_TOTAL;
    cfg.stream = stream;

    static int ncl = 0;
    static Scratch* scratch = nullptr;
    static CUtensorMap wo_map, wo_map48;
    static const void* wo_mapped = nullptr;
    static bool maps_ok = false;
    if (ncl == 0) {
        int n = 0;
        cfg.gridDim = dim3(MAX_CL * CL);
        if (cudaFuncSetAttribute(gqa_decode_kernel, cudaFuncAttributeMaxDynamicSharedMemorySize, SM_TOTAL) != cudaSuccess ||
            cudaGetSymbolAddress((void**)&scratch, g_scratch) != cudaSuccess ||
            cudaOccupancyMaxActiveClusters(&n, gqa_decode_kernel, &cfg) != cudaSuccess) {
            (void)cudaGetLastError();
            n = 0;
        }
        ncl = n > MAX_CL ? MAX_CL : (n < MIN_CL ? -1 : n);
    }
    if (wo_mapped != (const void*)wo) {
        typedef CUresult (*EncodeFn)(CUtensorMap*, CUtensorMapDataType, cuuint32_t, void*, const cuuint64_t*,
                                     const cuuint64_t*, const cuuint32_t*, const cuuint32_t*, CUtensorMapInterleave,
                                     CUtensorMapSwizzle, CUtensorMapL2promotion, CUtensorMapFloatOOBfill);
        void* fn = nullptr;
        cudaDriverEntryPointQueryResult st;
        maps_ok = cudaGetDriverEntryPoint("cuTensorMapEncodeTiled", &fn, cudaEnableDefault, &st) == cudaSuccess && fn;
        const cuuint64_t gdim[2] = {(cuuint64_t)D_MODEL, (cuuint64_t)QCOLS};
        const cuuint64_t gstr[1] = {(cuuint64_t)D_MODEL * 2};
        const cuuint32_t box16[2] = {16, 256}, box48[2] = {48, 256}, estr[2] = {1, 1};
        for (int k = 0; k < 2 && maps_ok; k++)
            maps_ok = ((EncodeFn)fn)(k ? &wo_map48 : &wo_map, CU_TENSOR_MAP_DATA_TYPE_BFLOAT16, 2, d_in[4], gdim, gstr,
                                     k ? box48 : box16, estr, CU_TENSOR_MAP_INTERLEAVE_NONE, CU_TENSOR_MAP_SWIZZLE_NONE,
                                     CU_TENSOR_MAP_L2_PROMOTION_L2_128B, CU_TENSOR_MAP_FLOAT_OOB_FILL_NONE) == CUDA_SUCCESS;
        wo_mapped = (const void*)wo;
    }
    if (ncl > 0 && maps_ok) {
        cfg.gridDim = dim3(ncl * CL);
        cudaLaunchKernelEx(&cfg, gqa_decode_kernel, ncl, 0u, kc, vc, wq, x, scratch, wo, out, wo_map, wo_map48);
    } else {
        fb_q_kernel<<<QCOLS / 128, 128, 0, stream>>>(x, wq);
        fb_attn_kernel<<<dim3(FB_SPLIT, HKV), 64, 0, stream>>>(kc, vc);
        fb_combine_kernel<<<HQ, DH, 0, stream>>>();
        fb_out_kernel<<<D_MODEL / 64, 64, 0, stream>>>(wo, out);
    }
}
```

```cpp
#include <cuda_runtime.h>
#include <cuda.h>
#include <cuda_bf16.h>
#include <stdint.h>

namespace {

constexpr int D_MODEL = 576;
constexpr int HQ = 32;
constexpr int HKV = 16;
constexpr int SK = 65536;
constexpr int DH = 128;
constexpr int QCOLS = HQ * DH;

constexpr int TILE_KEYS = 64;
constexpr int TILE_BYTES = TILE_KEYS * DH * 2;
constexpr int TILES_PER_HEAD = SK / TILE_KEYS;
constexpr int NTILES = TILES_PER_HEAD * HKV;
#define GQA_STAGES 6
#define GQA_INFL 3
#define GQA_INIT 1
#define GQA_PACE 87
#define GQA_D1 4000
#define GQA_D2 2000
#define GQA_PFIRST 1
#define GQA_NPAIR 3
#define GQA_W0 1
#define GQA_W1 2
#define GQA_W2 2
#define GQA_PFN 3
#define GQA_HINT 1000
constexpr int STAGES = GQA_STAGES;
constexpr int INFL = GQA_INFL;
constexpr int INIT = GQA_INIT;

constexpr int CL = 8;
constexpr int NSR = 5;
constexpr int NAR = CL - NSR;
constexpr int MAX_CL = 16, MIN_CL = 12;
constexpr int NPAIR = GQA_NPAIR;
constexpr int NCONS = 2 * NPAIR;
constexpr int NTHREADS = 8 * 32;
constexpr int NQITEM = QCOLS / 64;
constexpr int QROWS = D_MODEL / NAR;
constexpr int QLEAD = 2;
constexpr int NOWN = D_MODEL / 16;
constexpr int NSLOT = NSR * NCONS;
constexpr uint32_t MERGE_BYTES = NSLOT * 1024, ML_BYTES = NSLOT * 16;

constexpr int SS_STAGE = 0;
constexpr int STAGE_BYTES = 2 * TILE_BYTES;
constexpr int SS_Q = SS_STAGE + STAGES * STAGE_BYTES;
constexpr int DEFK = 3;
constexpr int DEF = DEFK * NSR;
static_assert(DEF == HKV - 1 && DEFK <= NPAIR, "all heads but the last are projected late, one per warp pair");
constexpr int SS_O = SS_Q + QCOLS * 2;
constexpr int SS_BAR = SS_O + 3 * 512;
constexpr int SS_BARO = SS_BAR + (3 * STAGES + HKV + NAR) * 8;
constexpr int METAS = 16;
constexpr int SS_META = SS_BARO + 3 * 8;
constexpr int SS_TOTAL = SS_META + METAS * 4;
constexpr int WO_BOX = 256 * 96;
constexpr int SA_WO = 0;
constexpr int SA_SLOT = SA_WO + 4 * WO_BOX;
constexpr int SA_ML = SA_SLOT + NSLOT * 1024;
constexpr int SA_BAR = SA_ML + 2 * NSLOT * 8;
constexpr int SA_BARML = SA_BAR + 8;
constexpr int INBOX = SA_BARML + 8 - SA_SLOT;
constexpr int SA_QRED = SA_SLOT + 2 * INBOX;
constexpr int SA_O = SA_QRED + QLEAD * NAR * 8 * 256;
constexpr int SA_ORED = SA_O + 512;
constexpr int SA_WT = SA_ORED + 16 * 32 * 4;
constexpr int SA_LSE = SA_WT + 4 * 32 * 4;
constexpr int SA_BARDEF = SA_LSE + 128;
constexpr int SA_BARWO = SA_BARDEF + 8;
constexpr int SA_BARQ = SA_BARWO + 8;
constexpr int SA_TOTAL = SA_BARQ + QLEAD * 8;
static_assert(INBOX % 16 == 0 && SA_SLOT % 16 == 0, "alignment");
constexpr int SM_TOTAL = SS_TOTAL > SA_TOTAL ? SS_TOTAL : SA_TOTAL;

constexpr uint32_t SPIN_LIMIT = 1u << 22;

struct Scratch {
    uint4 part[HKV - 1][MAX_CL][128];
    uint4 ypk[NOWN][MAX_CL][16];
    unsigned long long qpk[QCOLS / 2];
    unsigned int epoch;
    unsigned int pad0[31];
    unsigned int ticket;
    unsigned int pad1[31];
};
__device__ __align__(128) Scratch g_scratch;

#define TRACE(slot) do { } while (0)
#define PROG(t) do { } while (0)

__device__ __forceinline__ uint32_t smem_u32(const void* p) { return (uint32_t)__cvta_generic_to_shared(p); }
__device__ __forceinline__ uint32_t pin(uint32_t v) {
    asm volatile("mov.b32 %0, %0;" : "+r"(v));
    return v;
}
template <typename T>
__device__ __forceinline__ T* pin(T* p) {
    asm volatile("mov.b64 %0, %0;" : "+l"(p));
    return p;
}
__device__ __forceinline__ uint32_t mapa(uint32_t a, uint32_t rank) {
    uint32_t r;
    asm("mapa.shared::cluster.u32 %0, %1, %2;" : "=r"(r) : "r"(a), "r"(rank));
    return r;
}
__device__ __forceinline__ void mbar_init(uint32_t bar, uint32_t cnt) {
    asm volatile("mbarrier.init.shared::cta.b64 [%0], %1;" ::"r"(bar), "r"(cnt) : "memory");
}
__device__ __forceinline__ void mbar_expect_tx(uint32_t bar, uint32_t bytes) {
    asm volatile("mbarrier.arrive.expect_tx.shared::cta.b64 _, [%0], %1;" ::"r"(bar), "r"(bytes) : "memory");
}
__device__ __forceinline__ void mbar_arrive(uint32_t bar) {
    asm volatile("mbarrier.arrive.shared::cta.b64 _, [%0];" ::"r"(bar) : "memory");
}
__device__ __forceinline__ void mbar_arrive_remote(uint32_t cbar) {
    asm volatile("mbarrier.arrive.release.cluster.shared::cluster.b64 _, [%0];" ::"r"(cbar) : "memory");
}
__device__ __forceinline__ bool mbar_try_for(uint32_t bar, uint32_t parity, uint32_t ns) {
    uint32_t ok;
    asm volatile(
        "{\n.reg .pred p;\nmbarrier.try_wait.parity.shared::cta.b64 p, [%1], %2, %3;\nselp.u32 %0, 1, 0, p;\n}"
        : "=r"(ok) : "r"(bar), "r"(parity), "r"(ns) : "memory");
    return ok != 0;
}
__device__ __forceinline__ void mbar_wait(uint32_t bar, uint32_t parity) {
    uint32_t n = 0;
    while (!mbar_try_for(bar, parity, GQA_HINT)) {
        if (++n > SPIN_LIMIT) __trap();
    }
}
__device__ __forceinline__ void cluster_arrive_relaxed() { asm volatile("barrier.cluster.arrive.relaxed.aligned;" ::: "memory"); }
__device__ __forceinline__ void cluster_wait() { asm volatile("barrier.cluster.wait.acquire.aligned;" ::: "memory"); }
__device__ __forceinline__ void st_async_v4(uint32_t caddr, float a, float b, float c, float d, uint32_t cbar) {
    asm volatile("st.async.weak.shared::cluster.mbarrier::complete_tx::bytes.v4.f32 [%0], {%1,%2,%3,%4}, [%5];"
                 ::"r"(caddr), "f"(a), "f"(b), "f"(c), "f"(d), "r"(cbar) : "memory");
}
__device__ __forceinline__ void st_async_v2(uint32_t caddr, uint32_t a, uint32_t b, uint32_t cbar) {
    asm volatile("st.async.weak.shared::cluster.mbarrier::complete_tx::bytes.v2.b32 [%0], {%1,%2}, [%3];"
                 ::"r"(caddr), "r"(a), "r"(b), "r"(cbar) : "memory");
}
__device__ __forceinline__ void st_async_b32(uint32_t caddr, uint32_t a, uint32_t cbar) {
    asm volatile("st.async.weak.shared::cluster.mbarrier::complete_tx::bytes.b32 [%0], %1, [%2];"
                 ::"r"(caddr), "r"(a), "r"(cbar) : "memory");
}
__device__ __forceinline__ void bulk_load(uint32_t dst, const void* src, uint32_t bytes, uint32_t bar, uint64_t pol) {
    asm volatile(
        "cp.async.bulk.shared::cluster.global.mbarrier::complete_tx::bytes.L2::cache_hint [%0], [%1], %2, [%3], %4;"
        ::"r"(dst), "l"(src), "r"(bytes), "r"(bar), "l"(pol) : "memory");
}
__device__ __forceinline__ void l2_prefetch(const void* src, uint32_t bytes) {
    asm volatile("cp.async.bulk.prefetch.L2.global [%0], %1;" ::"l"(src), "r"(bytes) : "memory");
}
__device__ __forceinline__ void tma_load_2d(uint32_t dst, const CUtensorMap* tm, int c0, int c1, uint32_t bar) {
    asm volatile("cp.async.bulk.tensor.2d.shared::cluster.global.mbarrier::complete_tx::bytes [%0], [%1, {%3, %4}], [%2];"
                 ::"r"(dst), "l"(tm), "r"(bar), "r"(c0), "r"(c1) : "memory");
}
__device__ __forceinline__ uint4 lds128(uint32_t a) {
    uint4 v;
    asm volatile("ld.shared.v4.u32 {%0,%1,%2,%3}, [%4];" : "=r"(v.x), "=r"(v.y), "=r"(v.z), "=r"(v.w) : "r"(a) : "memory");
    return v;
}
__device__ __forceinline__ uint32_t lds32(uint32_t a) {
    uint32_t v;
    asm volatile("ld.shared.b32 %0, [%1];" : "=r"(v) : "r"(a) : "memory");
    return v;
}
__device__ __forceinline__ float2 lds64f(uint32_t a) {
    float2 v;
    asm volatile("ld.shared.v2.f32 {%0,%1}, [%2];" : "=f"(v.x), "=f"(v.y) : "r"(a) : "memory");
    return v;
}
__device__ __forceinline__ void sts32(uint32_t a, uint32_t v) { asm volatile("st.shared.b32 [%0], %1;" ::"r"(a), "r"(v) : "memory"); }
__device__ __forceinline__ float4 lds128f(uint32_t a) {
    float4 v;
    asm volatile("ld.shared.v4.f32 {%0,%1,%2,%3}, [%4];" : "=f"(v.x), "=f"(v.y), "=f"(v.z), "=f"(v.w) : "r"(a) : "memory");
    return v;
}
__device__ __forceinline__ uint4 ldsm_x4_trans(uint32_t a) {
    uint4 v;
    asm volatile("ldmatrix.sync.aligned.m8n8.x4.trans.shared.b16 {%0,%1,%2,%3}, [%4];"
                 : "=r"(v.x), "=r"(v.y), "=r"(v.z), "=r"(v.w) : "r"(a) : "memory");
    return v;
}
__device__ __forceinline__ void mma_bf16(float (&c)[4], uint32_t a0, uint32_t a1, uint32_t a2, uint32_t a3,
                                         uint32_t b0, uint32_t b1) {
    asm volatile(
        "mma.sync.aligned.m16n8k16.row.col.f32.bf16.bf16.f32 {%0,%1,%2,%3}, {%4,%5,%6,%7}, {%8,%9}, {%0,%1,%2,%3};"
        : "+f"(c[0]), "+f"(c[1]), "+f"(c[2]), "+f"(c[3])
        : "r"(a0), "r"(a1), "r"(a2), "r"(a3), "r"(b0), "r"(b1));
}
__device__ __forceinline__ uint4 ldg_nc128(const void* p) {
    uint4 v;
    asm volatile("ld.global.nc.L1::no_allocate.L2::128B.v4.u32 {%0,%1,%2,%3}, [%4];"
                 : "=r"(v.x), "=r"(v.y), "=r"(v.z), "=r"(v.w) : "l"(p));
    return v;
}
__device__ __forceinline__ uint32_t ld_relaxed32(const void* p) {
    uint32_t v;
    asm volatile("ld.relaxed.gpu.global.b32 %0, [%1];" : "=r"(v) : "l"(p) : "memory");
    return v;
}
__device__ __forceinline__ void st_relaxed64(void* p, unsigned long long v) {
    asm volatile("st.relaxed.gpu.global.b64 [%0], %1;" ::"l"(p), "l"(v) : "memory");
}
__device__ __forceinline__ void ld_relaxed64x2(const void* p, unsigned long long& lo, unsigned long long& hi) {
    asm volatile("ld.relaxed.gpu.global.v2.b64 {%0, %1}, [%2];" : "=l"(lo), "=l"(hi) : "l"(p) : "memory");
}
__device__ __forceinline__ void ld_relaxed128(const void* p, unsigned long long& lo, unsigned long long& hi) {
    asm volatile("{\n.reg .b128 t;\nld.relaxed.gpu.global.b128 t, [%2];\nmov.b128 {%0, %1}, t;\n}"
                 : "=l"(lo), "=l"(hi) : "l"(p) : "memory");
}
__device__ __forceinline__ void st_relaxed128(void* p, unsigned long long lo, unsigned long long hi) {
    asm volatile("{\n.reg .b128 t;\nmov.b128 t, {%1, %2};\nst.relaxed.gpu.global.b128 [%0], t;\n}"
                 ::"l"(p), "l"(lo), "l"(hi) : "memory");
}
__device__ __forceinline__ float ex2(float x) {
    float y;
    asm("ex2.approx.ftz.f32 %0, %1;" : "=f"(y) : "f"(x));
    return y;
}
__device__ __forceinline__ float rcp(float x) {
    float y;
    asm("rcp.approx.ftz.f32 %0, %1;" : "=f"(y) : "f"(x));
    return y;
}
__device__ __forceinline__ float warp_max(float v) {
    int k = __float_as_int(v);
    k ^= (k >> 31) & 0x7fffffff;
    k = __reduce_max_sync(0xffffffffu, k);
    k ^= (k >> 31) & 0x7fffffff;
    return __int_as_float(k);
}
__device__ __forceinline__ uint32_t pack_bf16(float lo, float hi) {
    uint32_t r;
    asm("cvt.rn.bf16x2.f32 %0, %1, %2;" : "=r"(r) : "f"(hi), "f"(lo));
    return r;
}
__device__ __forceinline__ float bf_lo(uint32_t v) { return __uint_as_float(v << 16); }
__device__ __forceinline__ float bf_hi(uint32_t v) { return __uint_as_float(v & 0xffff0000u); }
__device__ __forceinline__ void named_sync(int id, int n) { asm volatile("bar.sync %0, %1;" ::"r"(id), "r"(n) : "memory"); }
__device__ __forceinline__ void fma8(float* a, float s, const uint4& w) {
    a[0] = fmaf(s, bf_lo(w.x), a[0]); a[1] = fmaf(s, bf_hi(w.x), a[1]);
    a[2] = fmaf(s, bf_lo(w.y), a[2]); a[3] = fmaf(s, bf_hi(w.y), a[3]);
    a[4] = fmaf(s, bf_lo(w.z), a[4]); a[5] = fmaf(s, bf_hi(w.z), a[5]);
    a[6] = fmaf(s, bf_lo(w.w), a[6]); a[7] = fmaf(s, bf_hi(w.w), a[7]);
}

template <int AHEAD>
__global__ void __cluster_dims__(CL, 1, 1) __launch_bounds__(NTHREADS, 1)
gqa_decode_kernel(int ncl, uint32_t zero, const __nv_bfloat16* __restrict__ kc, const __nv_bfloat16* __restrict__ vc,
                  const __nv_bfloat16* __restrict__ wq, const __nv_bfloat16* __restrict__ x, Scratch* __restrict__ sc,
                  const __nv_bfloat16* __restrict__ wo, __nv_bfloat16* __restrict__ out,
                  const __grid_constant__ CUtensorMap wo_map48) {
    extern __shared__ __align__(1024) unsigned char smem[];
    const uint32_t sb = smem_u32(smem);
    const int tid = threadIdx.x, warp = tid >> 5, lane = tid & 31;
    const int rank = blockIdx.x % CL, cl = blockIdx.x / CL;
    constexpr float SCL = 0.08838834764831845f * 1.4426950408889634f;

    if (rank < NSR) {
        const uint32_t bar_full = sb + SS_BAR, bar_empty = bar_full + STAGES * 8;
        const uint32_t bar_q = bar_empty + STAGES * 8, bar_free = bar_q + HKV * 8, bar_fk = bar_free + NAR * 8;
        volatile uint32_t* meta = reinterpret_cast<volatile uint32_t*>(smem + SS_META);
        if (warp > NCONS + 1) return;
        if (warp == NCONS + 1) {
            const uint32_t tag = ld_relaxed32(&sc->epoch) + 1u;
            if (lane == 0) {
#pragma unroll
                for (int a = 0; a < NAR; a++) mbar_init(bar_free + a * 8, 1);
#pragma unroll
                for (int k = 0; k < DEFK; k++) mbar_init(sb + SS_BARO + k * 8, 1);
                asm volatile("fence.mbarrier_init.release.cluster;" ::: "memory");
            }
            __syncwarp();
            cluster_arrive_relaxed();
            if (lane == 0) {
#pragma unroll
                for (int h = 0; h < HKV; h++) mbar_init(bar_q + h * 8, 32);
#pragma unroll
                for (int k = 0; k < DEFK; k++) mbar_expect_tx(sb + SS_BARO + k * 8, 512);
            }
            __syncwarp();
            asm volatile("bar.arrive 1, %0;" ::"n"((NCONS + 2) * 32) : "memory");
#pragma unroll 1
            for (int h = 0; h < HKV; h++) {
                unsigned long long lo[2], hi[2];
                uint32_t n = 0;
                while (true) {
                    bool ok = true;
#pragma unroll
                    for (int k = 0; k < 2; k++) {
                        ld_relaxed64x2(&sc->qpk[h * 128 + (k * 32 + lane) * 2], lo[k], hi[k]);
                        ok = ok && ((uint32_t)(lo[k] >> 32) == tag) && ((uint32_t)(hi[k] >> 32) == tag);
                    }
                    if (ok) break;
                    if (h > 0) __nanosleep(500);
                    if (++n > SPIN_LIMIT) __trap();
                }
#pragma unroll
                for (int k = 0; k < 2; k++)
                    *reinterpret_cast<uint2*>(smem + SS_Q + h * 512 + (k * 32 + lane) * 8) = make_uint2((uint32_t)lo[k], (uint32_t)hi[k]);
                mbar_arrive(bar_q + h * 8);
            }
            return;
        }
        if (warp == NCONS) {
            const int ns = ncl * NSR, sid = cl * NSR + rank;
            const int pace = GQA_PACE * ncl;
            uint64_t pol = 0;
            const char* kp = reinterpret_cast<const char*>(kc);
            const char* vp = reinterpret_cast<const char*>(vc);
            auto issue_k = [&](int i, int s, int t) {
                PROG(t);
                mbar_expect_tx(bar_fk + s * 8, TILE_BYTES);
                bulk_load(sb + SS_STAGE + s * STAGE_BYTES, kp + (size_t)t * TILE_BYTES, TILE_BYTES, bar_fk + s * 8, pol);
                meta[(i + 1) % METAS] = ((uint32_t)(i + 1) << 5) | (uint32_t)(t / TILES_PER_HEAD);
            };
            auto issue_v = [&](int s, int t) {
                mbar_expect_tx(bar_full + s * 8, TILE_BYTES);
                bulk_load(sb + SS_STAGE + s * STAGE_BYTES + TILE_BYTES, vp + (size_t)t * TILE_BYTES, TILE_BYTES, bar_full + s * 8, pol);
            };
            auto issue = [&](int i, int s, int t) { issue_k(i, s, t); issue_v(s, t); };
            if (lane == 0) TRACE(0);
            if (lane == 0) {
                l2_prefetch(kp + (size_t)sid * TILE_BYTES, TILE_BYTES);
                l2_prefetch(vp + (size_t)sid * TILE_BYTES, TILE_BYTES);
            }
            if (lane < METAS) meta[lane] = 0;
            __syncwarp();
            long long t_start = 0;
            if (lane == 0) {
#pragma unroll
                for (int s = 0; s < STAGES; s++) {
                    mbar_init(bar_full + s * 8, 1);
                    mbar_init(bar_fk + s * 8, 1);
                    mbar_init(bar_empty + s * 8, 2);
                }
                asm volatile("fence.proxy.async.shared::cta;" ::: "memory");
                asm volatile("createpolicy.fractional.L2::evict_first.b64 %0, 1.0;" : "=l"(pol));
                t_start = clock64();
#pragma unroll
                for (int s = 0; s < INIT; s++) issue(s, s, sid + s * ns);
                TRACE(1);
            }
            __syncwarp();
            asm volatile("bar.arrive 1, %0;" ::"n"((NCONS + 2) * 32) : "memory");
            cluster_arrive_relaxed();
            if (lane == 0) {
#pragma unroll 1
                for (int s = INIT; s < STAGES; s++) {
                    while (clock64() - t_start < (long long)((s - INIT + 1) * pace)) { }
                    issue(s, s, sid + s * ns);
                }
#pragma unroll 1
                for (int k = 0; k < GQA_PFN; k++) {
                    bool freed = false;
                    while (clock64() - t_start < (long long)((STAGES - INIT + 1 + k) * pace) && !freed)
                        freed = mbar_try_for(bar_empty, 0, 64);
                    if (freed) break;
                    l2_prefetch(kp + (size_t)(sid + (STAGES + k) * ns) * TILE_BYTES, TILE_BYTES);
                    l2_prefetch(vp + (size_t)(sid + (STAGES + k) * ns) * TILE_BYTES, TILE_BYTES);
                }
                TRACE(52);
                constexpr int NSTATIC = STAGES + (GQA_PFN > AHEAD ? GQA_PFN : AHEAD);
                const int base = NSTATIC * ns;
                int tk[AHEAD];
#pragma unroll
                for (int k = 0; k < AHEAD; k++) tk[k] = sid + (STAGES + k) * ns;
                int tprev = -1;
                int i = STAGES;
                int s = 0, sv = STAGES - 1;
                uint32_t ph = 1;
                int sp = STAGES - INFL, spv = STAGES - INFL - 1;
                uint32_t php = 0, phv = 0;
                bool done = false;
                while (!done) {
#pragma unroll
                    for (int u = 0; u < AHEAD; u++) {
                        const int t = tk[u];
                        if (t < NTILES) {
                            mbar_wait(bar_empty + s * 8, ph ^ 1);
                            mbar_wait(bar_fk + sp * 8, php);
                            issue_k(i, s, t);
                            if (i < STAGES + 6) TRACE(53 + i - STAGES);
                            tk[u] = (i + AHEAD < NSTATIC) ? t + AHEAD * ns : base + (int)atomicAdd(&sc->ticket, 1u);
                        } else {
                            int neg = 0;
#pragma unroll
                            for (int k = 0; k < AHEAD; k++) neg |= tk[k];
#pragma unroll
                            for (int k = 0; k < NPAIR; k++)
                                meta[(i + 1 + k) % METAS] = (((uint32_t)(i + 1 + k) << 5) | (uint32_t)(HKV + k)) + (neg < 0);
                            done = true;
                            if (DEFK > 0) asm volatile("prefetch.tensormap [%0];" ::"l"(&wo_map48) : "memory");
                        }
                        if (tprev >= 0) {
                            mbar_wait(bar_full + spv * 8, phv);
                            issue_v(sv, tprev);
                        }
                        if (done) break;
                        tprev = t;
                        sv = s;
                        spv = sp;
                        phv = php;
                        i++;
                        if (++s == STAGES) { s = 0; ph ^= 1; }
                        if (++sp == STAGES) { sp = 0; php ^= 1; }
                    }
                }
                int landed = 0;
                auto wait_landed = [&](int w) {
                    for (; landed < w; landed++) {
                        mbar_wait(bar_full + sp * 8, php);
                        if (++sp == STAGES) { sp = 0; php ^= 1; }
                    }
                };
                if (cl < NOWN / NAR) {
#pragma unroll
                    for (int k = 0; k < DEFK; k++) {
                        wait_landed(k == 0 ? GQA_W0 : k == 1 ? GQA_W1 : GQA_W2);
                        if (k == 0) TRACE(14);
                        mbar_wait(bar_empty + s * 8, ph ^ 1);
                        mbar_expect_tx(bar_fk + s * 8, WO_BOX);
                        tma_load_2d(sb + SS_STAGE + s * STAGE_BYTES, &wo_map48, cl * 48, (k * NSR + rank) * 256, bar_fk + s * 8);
                        if (++s == STAGES) { s = 0; ph ^= 1; }
                    }
                }
            }
            return;
        }
        cluster_arrive_relaxed();
        const int g = lane >> 2, t4 = lane & 3;
        const uint32_t koff = ((warp & 1) * 32 + g) * 256 + t4 * 16 + (g & 1) * 64;
        const uint32_t qoff = (g >> 2) * 256 + t4 * 16 + (((g >> 1) ^ g) & 1) * 64;
        const int kk = lane & 7, mi = lane >> 3;
        const uint32_t voff = TILE_BYTES + ((warp & 1) * 32 + 2 * (kk >> 1) + (mi >> 1) + 8 * (kk & 1)) * 256 +
                              ((mi ^ kk) & 1) * 16 + (kk >> 1) * 32;
        const int slot = rank * NCONS + warp;
        const uint32_t ka0 = pin(sb + SS_STAGE + koff), ka1 = pin(sb + SS_STAGE + (koff ^ 64));
        const uint32_t va0 = pin(sb + SS_STAGE + voff), va1 = pin(sb + SS_STAGE + (voff ^ 32));
        const uint32_t va2 = pin(sb + SS_STAGE + (voff ^ 64)), va3 = pin(sb + SS_STAGE + (voff ^ 96));
        const uint32_t bars = pin(bar_full), metas = pin(sb + SS_META);
        const uint32_t src0 = pin(8 * t4 + 2 * (g >> 2));
        const uint32_t bmask = pin(t4 == (g & 3) ? 0xffffffffu : 0u);
        const uint32_t oddm = pin((g ^ t4) & 1);
        const uint32_t zr = pin(zero), ln = pin(lane);
        const uint32_t poff = pin(SA_SLOT + slot * 1024 + (t4 >> 1) * 512 + (g * 2 + (t4 & 1)) * 16);
        const uint32_t mloff = pin((g == 0 && (t4 & 1) == 0) ? SA_ML + ((t4 >> 1) * NSLOT + slot) * 8 : 0);
        named_sync(1, (NCONS + 2) * 32);

        constexpr uint32_t FK = (2 * STAGES + HKV + NAR) * 8, EM = STAGES * 8;
        static_assert(STAGES % NPAIR == 0 && NSLOT <= 32, "a warp pair owns every NPAIR-th stage");
        int s = warp >> 1;
        uint32_t ph = 0, seq = 1 + (warp >> 1);
        int th = 0;
#pragma unroll 1
        for (int h = 0; h < HKV; h++) {
            mbar_wait(bar_q + h * 8, 0);
            if (h == 0 && tid == 0) TRACE(3);
            uint4 qf[4];
#pragma unroll
            for (int j = 0; j < 4; j++) qf[j] = lds128(sb + SS_Q + h * 512 + (qoff ^ (j * 64)));
            float acc[8][4];
#pragma unroll
            for (int i = 0; i < 8; i++) { acc[i][0] = acc[i][1] = acc[i][2] = acc[i][3] = 0.f; }
            float m = -INFINITY, l = 0.f, lsum = 0.f;
            bool ml_sent = false;
            if (h == 0) cluster_wait();
            const bool last = (h == HKV - 1);
            if (h >= NAR && !last) mbar_wait(bar_free + (h % NAR) * 8, (uint32_t)(h / NAR - 1) & 1u);
            const uint32_t rb_ = pin(mapa(sb, NSR + h % NAR) + (last ? INBOX : 0));
            const uint32_t rb1 = pin(last ? mapa(sb, NSR + 1) + INBOX : 0u), rb2 = pin(mapa(sb, NSR + 2) + INBOX);
            auto send_ml = [&]() {
                if (mloff) {
                    st_async_v2(rb_ + mloff, __float_as_uint(m), __float_as_uint(lsum), rb_ + SA_BARML);
                    if (rb1) {
                        st_async_v2(rb1 + mloff, __float_as_uint(m), __float_as_uint(lsum), rb1 + SA_BARML);
                        st_async_v2(rb2 + mloff, __float_as_uint(m), __float_as_uint(lsum), rb2 + SA_BARML);
                    }
                }
            };
            while (th == h) {
                const uint32_t so = s * STAGE_BYTES, bv = bars + s * 8, pvh = ph;
                float sc[4];
                {
                    const uint32_t a0 = ka0 + so, a1 = ka1 + so;
                    mbar_wait(bv + FK, pvh);
#pragma unroll
                    for (int u = 0; u < 2; u++) {
                        uint4 ra[4], rb[4];
                        ra[0] = lds128(a0 + u * 4096); rb[0] = lds128(a0 + u * 4096 + 2048);
                        ra[1] = lds128(a1 + u * 4096); rb[1] = lds128(a1 + u * 4096 + 2048);
                        ra[2] = lds128(a0 + u * 4096 + 128); rb[2] = lds128(a0 + u * 4096 + 2048 + 128);
                        ra[3] = lds128(a1 + u * 4096 + 128); rb[3] = lds128(a1 + u * 4096 + 2048 + 128);
                        float c0[4] = {0.f, 0.f, 0.f, 0.f}, c1[4] = {0.f, 0.f, 0.f, 0.f};
#pragma unroll
                        for (int j = 0; j < 4; j++) {
                            mma_bf16(c0, ra[j].x, rb[j].x, ra[j].y, rb[j].y, qf[j].x, qf[j].y);
                            mma_bf16(c1, ra[j].z, rb[j].z, ra[j].w, rb[j].w, qf[j].z, qf[j].w);
                        }
                        sc[2 * u] = oddm ? (c0[1] + c1[1]) : (c0[0] + c1[0]);
                        sc[2 * u + 1] = oddm ? (c0[3] + c1[3]) : (c0[2] + c1[2]);
                    }
                }
                float mx = fmaxf(fmaxf(sc[0], sc[1]), fmaxf(sc[2], sc[3]));
                mx = fmaxf(mx, __shfl_xor_sync(0xffffffffu, mx, 4));
                mx = fmaxf(mx, __shfl_xor_sync(0xffffffffu, mx, 8));
                mx = fmaxf(mx, __shfl_xor_sync(0xffffffffu, mx, 16));
                const float mn = fmaxf(m, mx);
                const float alpha = ex2((m - mn) * SCL);
                const float p0 = ex2((sc[0] - mn) * SCL), p1 = ex2((sc[1] - mn) * SCL);
                const float p2 = ex2((sc[2] - mn) * SCL), p3 = ex2((sc[3] - mn) * SCL);
                m = mn;
                l = fmaf(l, alpha, (p0 + p1) + (p2 + p3));
                const uint32_t pka = pack_bf16(p0, p1), pkb = pack_bf16(p2, p3);
                uint32_t bf[4];
                bf[0] = __shfl_sync(0xffffffffu, pka, src0) & bmask;
                bf[1] = __shfl_sync(0xffffffffu, pka, src0 + 4) & bmask;
                bf[2] = __shfl_sync(0xffffffffu, pkb, src0) & bmask;
                bf[3] = __shfl_sync(0xffffffffu, pkb, src0 + 4) & bmask;
#pragma unroll
                for (int i = 0; i < 8; i++) { acc[i][0] *= alpha; acc[i][1] *= alpha; acc[i][2] *= alpha; acc[i][3] *= alpha; }
                lsum = l + __shfl_xor_sync(0xffffffffu, l, 4);
                lsum += __shfl_xor_sync(0xffffffffu, lsum, 8);
                lsum += __shfl_xor_sync(0xffffffffu, lsum, 16);
                s += NPAIR;
                if (s >= STAGES) { s -= STAGES; ph ^= 1; }
                seq += NPAIR;
                const uint32_t a0 = va0 + so, a1 = va1 + so, a2 = va2 + so, a3 = va3 + so, ma = metas + (seq % METAS) * 4;
                uint32_t mt, dep = 0, n = 0;
                while (true) {
                    asm volatile("ld.volatile.shared.u32 %0, [%1];" : "=r"(mt) : "r"(ma) : "memory");
                    if ((mt >> 5) == seq) {
                        if ((int)(mt & 31u) != h) {
                            send_ml();
                            ml_sent = true;
                        }
                        mbar_wait(bv, pvh);
                        break;
                    }
                    if (mbar_try_for(bv, pvh, 128)) break;
                    if (++n > SPIN_LIMIT) __trap();
                }
                __syncwarp();
#pragma unroll
                for (int u = 0; u < 2; u++) {
                    uint4 va[8];
                    va[0] = ldsm_x4_trans(a0 + u * 4096); va[1] = ldsm_x4_trans(a1 + u * 4096);
                    va[2] = ldsm_x4_trans(a2 + u * 4096); va[3] = ldsm_x4_trans(a3 + u * 4096);
                    va[4] = ldsm_x4_trans(a0 + u * 4096 + 128); va[5] = ldsm_x4_trans(a1 + u * 4096 + 128);
                    va[6] = ldsm_x4_trans(a2 + u * 4096 + 128); va[7] = ldsm_x4_trans(a3 + u * 4096 + 128);
#pragma unroll
                    for (int i = 0; i < 8; i++)
                        mma_bf16(acc[i], __byte_perm(va[i].x, va[i].y, 0x7610), __byte_perm(va[i].y, va[i].x, 0x7610),
                                 __byte_perm(va[i].z, va[i].w, 0x7610), __byte_perm(va[i].w, va[i].z, 0x7610),
                                 bf[2 * u], bf[2 * u + 1]);
                    dep |= (va[0].x | va[1].x) | (va[2].x | va[3].x | va[4].x) | (va[5].x | va[6].x | va[7].x);
                }
                if (ln == 0) mbar_arrive(bv + EM + (dep & zr));
                n = 0;
                while ((mt >> 5) != seq) {
                    if (n) __nanosleep(32);
                    asm volatile("ld.volatile.shared.u32 %0, [%1];" : "=r"(mt) : "r"(ma) : "memory");
                    if (++n > SPIN_LIMIT) __trap();
                }
                th = (int)(mt & 31u);
            }
            if (!ml_sent) send_ml();
            float w[8];
#pragma unroll
            for (int k = 0; k < 4; k++) {
                const int i = (k & 1) | ((k & 2) << 1);
                w[2 * k] = (acc[i][0] + acc[i ^ 1][1]) + __shfl_xor_sync(0xffffffffu, acc[i ^ 2][0] + acc[i ^ 3][1], 1);
                w[2 * k + 1] = (acc[i][2] + acc[i ^ 1][3]) + __shfl_xor_sync(0xffffffffu, acc[i ^ 2][2] + acc[i ^ 3][3], 1);
            }
            st_async_v4(rb_ + poff, w[0], w[1], w[2], w[3], rb_ + SA_BAR);
            st_async_v4(rb_ + poff + 256, w[4], w[5], w[6], w[7], rb_ + SA_BAR);
            if (rb1) {
                st_async_v4(rb1 + poff, w[0], w[1], w[2], w[3], rb1 + SA_BAR);
                st_async_v4(rb1 + poff + 256, w[4], w[5], w[6], w[7], rb1 + SA_BAR);
                st_async_v4(rb2 + poff, w[0], w[1], w[2], w[3], rb2 + SA_BAR);
                st_async_v4(rb2 + poff + 256, w[4], w[5], w[6], w[7], rb2 + SA_BAR);
            }
            if (tid == 0) TRACE(16 + h);
        }
        if (DEFK > 0 && cl < NOWN / NAR && th - HKV < DEFK) {
            const int k = th - HKV;
            const uint32_t ab = sb + SS_STAGE + s * STAGE_BYTES +
                                ((warp & 1) * 128 + (lane >> 4) * 16 + ((lane >> 1) & 3) + (lane & 1) * 8) * 96 + ((lane >> 3) & 1) * 16;
            uint4 bo[4];
            mbar_wait(sb + SS_BARO + k * 8, 0);
#pragma unroll
            for (int i = 0; i < 4; i++) bo[i] = lds128(sb + SS_O + k * 512 + ((warp & 1) * 64 + i * 16 + t4 * 4) * 4);
            float d[3][2][4];
#pragma unroll
            for (int a = 0; a < 3; a++)
#pragma unroll
                for (int c = 0; c < 2; c++) d[a][c][0] = d[a][c][1] = d[a][c][2] = d[a][c][3] = 0.f;
            const uint32_t dsto = SA_ORED + (g * 32 + (k * NSR + rank) * 2 + (warp & 1)) * 4;
            mbar_wait(bars + FK + s * 8, ph);
#pragma unroll
            for (int i = 0; i < 4; i++) {
#pragma unroll
                for (int c = 0; c < 2; c++) {
#pragma unroll
                    for (int a = 0; a < 3; a++) {
                        const uint4 wf = ldsm_x4_trans(ab + ((i >> 1) * 64 + c * 32 + (i & 1) * 4) * 96 + a * 32);
                        mma_bf16(d[a][c], wf.x, wf.y, wf.z, wf.w, c ? bo[i].z : bo[i].x, c ? bo[i].w : bo[i].y);
                    }
                }
            }
            if (t4 == 0) {
#pragma unroll
                for (int a = 0; a < 3; a++) {
                    const uint32_t ra_ = mapa(sb, NSR + a);
                    st_async_b32(ra_ + dsto, __float_as_uint(d[a][0][0] + d[a][1][0]), ra_ + SA_BARDEF);
                    st_async_b32(ra_ + dsto + 8 * 32 * 4, __float_as_uint(d[a][0][2] + d[a][1][2]), ra_ + SA_BARDEF);
                }
            }
            if (lane == 0) TRACE(15);
        }
        return;
    }

    const int ar = rank - NSR, aid = cl * NAR + ar;
    const uint32_t bar_qred = sb + SA_BARQ;
    if (tid == 0) TRACE(4);
    const uint32_t tag = ld_relaxed32(&sc->epoch) + 1u;
    {
        const int row0 = ar * QROWS + (tid >> 3);
        const __nv_bfloat16* wp = wq + (size_t)row0 * QCOLS + (tid & 7) * 8;
        uint4 w[6];
#pragma unroll
        for (int i = 0; i < 6; i++) w[i] = ldg_nc128(wp + cl * 64 + (size_t)i * 32 * QCOLS);
        float xv[6];
#pragma unroll
        for (int i = 0; i < 6; i++) xv[i] = __bfloat162float(x[row0 + i * 32]);
        static_assert(QLEAD == 2, "8 barriers");
        const uint32_t mybar = sb + (warp < 4 ? SA_BAR + (warp & 1) * 8 + (warp >> 1) * INBOX : SA_BARDEF + (warp - 4) * 8);
        if (lane == 0) {
            mbar_init(mybar, 1);
            asm volatile("fence.mbarrier_init.release.cluster;" ::: "memory");
        }
        __syncwarp();
        cluster_arrive_relaxed();
        if (lane == 0)
            mbar_expect_tx(mybar, warp < 4 ? ((warp & 1) ? ML_BYTES : MERGE_BYTES)
                                           : warp == 4 ? DEF * 2 * 64 : warp == 5 ? 4 * WO_BOX : NAR * 8 * 256);
        __syncwarp();
        cluster_wait();
        int rnd = 0;
#pragma unroll 1
        for (int c = cl; c < NQITEM; c += ncl, rnd++) {
            if (rnd > 0) {
#pragma unroll
                for (int i = 0; i < 6; i++) w[i] = ldg_nc128(wp + c * 64 + (size_t)i * 32 * QCOLS);
            }
            float a[8];
#pragma unroll
            for (int k = 0; k < 8; k++) a[k] = 0.f;
#pragma unroll
            for (int i = 0; i < 6; i++) fma8(a, xv[i], w[i]);
            const bool u4 = lane & 16, u3 = lane & 8;
            float r4[4], r2[2];
#pragma unroll
            for (int k = 0; k < 4; k++)
                r4[k] = (u4 ? a[k + 4] : a[k]) + __shfl_xor_sync(0xffffffffu, u4 ? a[k] : a[k + 4], 16);
#pragma unroll
            for (int k = 0; k < 2; k++)
                r2[k] = (u3 ? r4[k + 2] : r4[k]) + __shfl_xor_sync(0xffffffffu, u3 ? r4[k] : r4[k + 2], 8);
            const int lead = rnd % NAR, lk = rnd / NAR;
            const uint32_t rb_ = mapa(sb, NSR + lead) + (tag & zero);
            st_async_v2(rb_ + SA_QRED + lk * (NAR * 8 * 256) + (ar * 8 + warp) * 256 + ((lane & 7) * 4 + (lane >> 3)) * 8,
                        __float_as_uint(r2[0]), __float_as_uint(r2[1]), rb_ + SA_BARQ + lk * 8);
            if (lead == ar) {
                if (warp == 0) {
                    mbar_wait(bar_qred + lk * 8, 0);
                    float s0 = 0.f, s1 = 0.f;
#pragma unroll
                    for (int k = 0; k < NAR * 8; k++) {
                        const float2 v = *reinterpret_cast<const float2*>(smem + SA_QRED + lk * (NAR * 8 * 256) + k * 256 + lane * 8);
                        s0 += v.x; s1 += v.y;
                    }
                    st_relaxed64(&sc->qpk[c * 32 + lane], (unsigned long long)pack_bf16(s0, s1) | ((unsigned long long)tag << 32));
                    if (rnd == 0 && lane == 0) TRACE(2);
                }
                named_sync(1, 256);
            }
            if (rnd == 0) {
                __nanosleep(GQA_D1);
                if (warp == 1) {
                    for (int r = aid + lane * ncl * NAR; r < D_MODEL; r += ncl * NAR * 32)
                        l2_prefetch(wq + (size_t)r * QCOLS + ncl * 64, (QCOLS - ncl * 64) * 2);
                    for (int r = DEF * NOWN + aid + lane * ncl * NAR; r < D_MODEL; r += ncl * NAR * 32)
                        l2_prefetch(wo + (size_t)r * QCOLS, QCOLS * 2);
                }
                __nanosleep(GQA_D2);
            }
        }
    }
    if (tid == 128) {
        asm volatile("fence.proxy.async.shared::cta;" ::: "memory");
#pragma unroll 1
        for (int k = 0; k < 4; k++)
            tma_load_2d(sb + SA_WO + k * WO_BOX, &wo_map48, ar * 192 + k * 48, (HKV - 1) * 256, sb + SA_BARWO);
    }
    __syncwarp();
    const int par = lane & 1;
    const bool has6 = 12 + par < ncl, has7 = 14 + par < ncl;
    auto fetch = [&](const uint4* src, int stride, unsigned long long (&lo)[8], unsigned long long (&hi)[8]) {
#pragma unroll
        for (int k = 0; k < 6; k++) ld_relaxed128(src + k * 2 * stride, lo[k], hi[k]);
        ld_relaxed128(src + (has6 ? 12 * stride : 0), lo[6], hi[6]);
        ld_relaxed128(src + (has7 ? 14 * stride : 0), lo[7], hi[7]);
    };
    auto complete = [&](uint32_t mask, const unsigned long long (&hi)[8]) -> bool {
        uint32_t bad = 0;
#pragma unroll
        for (int k = 0; k < 8; k++) bad |= (uint32_t)(hi[k] >> 32) ^ tag;
        return __all_sync(mask, bad == 0);
    };
    auto combine = [&](uint32_t mask, const unsigned long long (&lo)[8], const unsigned long long (&hi)[8]) -> float2 {
        float e[8];
#pragma unroll
        for (int k = 0; k < 8; k++) e[k] = __uint_as_float((uint32_t)lo[k]);
        if (!has6) e[6] = -INFINITY;
        if (!has7) e[7] = -INFINITY;
        float mx = fmaxf(fmaxf(fmaxf(e[0], e[1]), fmaxf(e[2], e[3])), fmaxf(fmaxf(e[4], e[5]), fmaxf(e[6], e[7])));
        mx = fmaxf(mx, __shfl_xor_sync(mask, mx, 1));
        float W = 0.f, o0 = 0.f, o1 = 0.f, W2 = 0.f, p0 = 0.f, p1 = 0.f;
#pragma unroll
        for (int k = 0; k < 8; k += 2) {
            const float wa = ex2(e[k] - mx), wb = ex2(e[k + 1] - mx);
            W += wa;
            o0 = fmaf(wa, __uint_as_float((uint32_t)(lo[k] >> 32)), o0);
            o1 = fmaf(wa, __uint_as_float((uint32_t)hi[k]), o1);
            W2 += wb;
            p0 = fmaf(wb, __uint_as_float((uint32_t)(lo[k + 1] >> 32)), p0);
            p1 = fmaf(wb, __uint_as_float((uint32_t)hi[k + 1]), p1);
        }
        W += W2; o0 += p0; o1 += p1;
        W += __shfl_xor_sync(mask, W, 1);
        o0 += __shfl_xor_sync(mask, o0, 1);
        o1 += __shfl_xor_sync(mask, o1, 1);
        const float inv = rcp(W);
        return make_float2(o0 * inv, o1 * inv);
    };
    uint4 wf[4][2][3];
    auto load_wf = [&]() {
        const uint32_t ab = sb + SA_WO + (warp >> 1) * WO_BOX +
                            ((warp & 1) * 128 + (lane >> 4) * 16 + ((lane >> 1) & 3) + (lane & 1) * 8) * 96 + ((lane >> 3) & 1) * 16;
        mbar_wait(sb + SA_BARWO, 0);
#pragma unroll
        for (int i = 0; i < 4; i++)
#pragma unroll
            for (int c = 0; c < 2; c++)
#pragma unroll
                for (int a = 0; a < 3; a++) wf[i][c][a] = ldsm_x4_trans(ab + ((i >> 1) * 64 + c * 32 + (i & 1) * 4) * 96 + a * 32);
    };
    const uint4* ysrc = &sc->ypk[aid < NOWN ? aid : 0][par][lane >> 1];
    unsigned long long ylo[8], yhi[8];
    if (warp < 4) {
        const uint32_t wb_addr = sb + SA_WT + warp * 128;
        uint4* dst = &sc->part[ar][cl][tid];
        uint32_t ph = 0;
#pragma unroll 1
        for (int h = ar;; h += NAR, dst += NAR * MAX_CL * 128) {
            const bool last = h >= HKV - 1;
            const uint32_t ib = sb + (last ? INBOX : 0);
            if (last) {
                ph = 0;
                load_wf();
            }
            mbar_wait(ib + SA_BARML, ph);
            float2 e = make_float2(-INFINITY, 0.f);
            if (lane < NSLOT) e = lds64f(ib + SA_ML + ((warp >> 1) * NSLOT + lane) * 8);
            float M = warp_max(e.x);
            const bool none = (M == -INFINITY);
            if (none) M = 0.f;
            const float wt = ex2((e.x - M) * SCL);
            float L = wt * e.y;
#pragma unroll
            for (int o = 16; o > 0; o >>= 1) L += __shfl_xor_sync(0xffffffffu, L, o);
            const float lse = none ? -INFINITY : fmaf(M, SCL, __log2f(L));
            sts32(wb_addr + lane * 4, __float_as_uint(none ? 0.f : wt * rcp(L)));
            if (last && (tid & 63) == 0) sts32(sb + SA_LSE + (warp >> 1) * 4, __float_as_uint(lse));
            __syncwarp();
            float wk[(NSLOT + 3) / 4 * 4];
#pragma unroll
            for (int k = 0; k < (NSLOT + 3) / 4; k++) {
                const float4 w4 = lds128f(wb_addr + k * 16);
                wk[4 * k] = w4.x; wk[4 * k + 1] = w4.y; wk[4 * k + 2] = w4.z; wk[4 * k + 3] = w4.w;
            }
            const uint32_t ua = ib + SA_SLOT + tid * 8;
            mbar_wait(ib + SA_BAR, ph);
            ph ^= 1;
            float o0 = 0.f, o1 = 0.f, p0 = 0.f, p1 = 0.f;
#pragma unroll
            for (int k = 0; k < NSLOT; k += 2) {
                const float2 ua0 = lds64f(ua + k * 1024), ua1 = lds64f(ua + (k + 1) * 1024);
                o0 = fmaf(wk[k], ua0.x, o0);     o1 = fmaf(wk[k], ua0.y, o1);
                p0 = fmaf(wk[k + 1], ua1.x, p0); p1 = fmaf(wk[k + 1], ua1.y, p1);
            }
            if (last) {
                sts32(sb + SA_O + tid * 4, pack_bf16(o0 + p0, o1 + p1));
                break;
            }
            st_relaxed128(dst, (unsigned long long)__float_as_uint(lse) | ((unsigned long long)__float_as_uint(o0 + p0) << 32),
                          (unsigned long long)__float_as_uint(o1 + p1) | ((unsigned long long)tag << 32));
            if (tid == 0) TRACE(32 + h);
            if (h + NAR < HKV - 1) {
                named_sync(2, 128);
                if (tid == 0) {
                    mbar_expect_tx(sb + SA_BAR, MERGE_BYTES);
                    mbar_expect_tx(sb + SA_BARML, ML_BYTES);
                }
                __syncwarp();
                if (tid < NSR) mbar_arrive_remote(mapa(sb + SS_BAR + (2 * STAGES + HKV + ar) * 8, tid));
            }
        }
    } else {
        if (aid < NOWN) {
            const int pj = (ar == 0 ? 0 : 2 + 42 * ar) + (warp - 4) * 11 + (lane >> 1);
            const bool comb = lane < 22 && pj < (ar == 2 ? 128 : 44 + 42 * ar);
            const uint32_t cmask = __ballot_sync(0xffffffffu, comb);
            const uint4* src = &sc->part[0][par][comb ? pj : 0];
            const int gate = ((lane >> 1) % 6) * 256;
            if (comb) {
#pragma unroll 1
                for (int h = 0; h < HKV - 1; h++, src += MAX_CL * 128) {
                    uint32_t n = 0;
                    while (true) {
                        ld_relaxed128(src + gate, ylo[0], yhi[0]);
                        if (__any_sync(cmask, (uint32_t)(yhi[0] >> 32) == tag)) break;
                        __nanosleep(500);
                        if (++n > SPIN_LIMIT) __trap();
                    }
                    do {
                        __nanosleep(500);
                        fetch(src, 128, ylo, yhi);
                        if (++n > SPIN_LIMIT) __trap();
                    } while (!complete(cmask, yhi));
                    const float2 o = combine(cmask, ylo, yhi);
                    const uint32_t rs = mapa(sb, h % NSR);
                    if (par == 0) st_async_b32(rs + SS_O + (h / NSR) * 512 + pj * 4, pack_bf16(o.x, o.y), rs + SS_BARO + (h / NSR) * 8);
                }
            }
            __syncwarp();
            if (warp == 4) fetch(ysrc, 16, ylo, yhi);
        }
        load_wf();
    }
    {
        const int g = lane >> 2, t4 = lane & 3;
        const uint32_t ba = pin(sb + SA_O + ((warp & 1) * 64 + t4 * 4) * 4), la = pin(sb + SA_LSE + (warp & 1) * 4);
        uint4* const ydst = pin(&sc->ypk[ar * 12 + (warp >> 1) * 3 + (t4 < 3 ? t4 : 0)][cl][(warp & 1) * 8 + g]);
        __nv_bfloat16* const outp = pin(out + aid * 16 + (lane >> 1) + par * 8);
        named_sync(3, 256);
        uint4 bo[4];
#pragma unroll
        for (int i = 0; i < 4; i++) bo[i] = lds128(ba + i * 64);
        const uint32_t lse = lds32(la);
        float d[3][2][4];
#pragma unroll
        for (int a = 0; a < 3; a++)
#pragma unroll
            for (int c = 0; c < 2; c++) d[a][c][0] = d[a][c][1] = d[a][c][2] = d[a][c][3] = 0.f;
#pragma unroll
        for (int i = 0; i < 4; i++)
#pragma unroll
            for (int c = 0; c < 2; c++)
#pragma unroll
                for (int a = 0; a < 3; a++)
                    mma_bf16(d[a][c], wf[i][c][a].x, wf[i][c][a].y, wf[i][c][a].z, wf[i][c][a].w, c ? bo[i].z : bo[i].x,
                             c ? bo[i].w : bo[i].y);
        const float y0 = t4 == 0 ? d[0][0][0] + d[0][1][0] : t4 == 1 ? d[1][0][0] + d[1][1][0] : d[2][0][0] + d[2][1][0];
        const float y1 = t4 == 0 ? d[0][0][2] + d[0][1][2] : t4 == 1 ? d[1][0][2] + d[1][1][2] : d[2][0][2] + d[2][1][2];
        if (t4 < 3)
            st_relaxed128(ydst, (unsigned long long)lse | ((unsigned long long)__float_as_uint(y0) << 32),
                          (unsigned long long)__float_as_uint(y1) | ((unsigned long long)tag << 32));
        if (tid == 0) TRACE(47);
        if (aid >= NOWN) return;
        if (warp == 5) {
            mbar_wait(sb + SA_BARDEF, 0);
            float t = 0.f;
#pragma unroll
            for (int k = 0; k < 4; k++) {
                const float4 v = lds128f(sb + SA_ORED + (lane >> 1) * 128 + par * 64 + k * 16);
                t += (par && k == 3) ? v.x + v.y : (v.x + v.y) + (v.z + v.w);
            }
            t += __shfl_xor_sync(0xffffffffu, t, 1);
            if (par == 0) sts32(sb + SA_LSE + 16 + (lane >> 1) * 4, __float_as_uint(t));
            __syncwarp();
            asm volatile("bar.arrive 4, 64;" ::: "memory");
        } else if (warp == 4) {
            uint32_t n = 0;
            while (!complete(0xffffffffu, yhi)) {
                fetch(ysrc, 16, ylo, yhi);
                if (++n > SPIN_LIMIT) __trap();
            }
            if (lane == 0) TRACE(8);
            const float2 y = combine(0xffffffffu, ylo, yhi);
            float r = par ? y.y : y.x;
            r += __shfl_xor_sync(0xffffffffu, r, 16);
            named_sync(4, 64);
            if (lane < 16) {
                r += __uint_as_float(lds32(sb + SA_LSE + 16 + ((lane >> 1) + par * 8) * 4));
                asm volatile("st.global.b16 [%0], %1;" ::"l"(outp), "h"(__bfloat16_as_ushort(__float2bfloat16(r))) : "memory");
            }
            if (lane == 0) TRACE(63);
            if (aid == 0 && lane == 0) {
                *reinterpret_cast<volatile unsigned int*>(&sc->epoch) = tag;
                *reinterpret_cast<volatile unsigned int*>(&sc->ticket) = 0u;
            }
        }
    }
}

constexpr int FB_SPLIT = 64;
__device__ float fb_q[QCOLS];
__device__ float fb_part[HQ][FB_SPLIT][DH + 2];
__device__ float fb_o[QCOLS];

__global__ void fb_q_kernel(const __nv_bfloat16* __restrict__ x, const __nv_bfloat16* __restrict__ wq) {
    const int c = blockIdx.x * blockDim.x + threadIdx.x;
    float a = 0.f;
    for (int i = 0; i < D_MODEL; i++) a = fmaf(__bfloat162float(x[i]), __bfloat162float(wq[(size_t)i * QCOLS + c]), a);
    fb_q[c] = __bfloat162float(__float2bfloat16(a));
}
__global__ void fb_attn_kernel(const __nv_bfloat16* __restrict__ kc, const __nv_bfloat16* __restrict__ vc) {
    const int sp = blockIdx.x, hq = blockIdx.y * 2 + (threadIdx.x >> 5), lane = threadIdx.x & 31;
    const size_t base = ((size_t)blockIdx.y * SK + (size_t)sp * (SK / FB_SPLIT)) * DH + lane * 4;
    const float4 q = *reinterpret_cast<const float4*>(&fb_q[hq * DH + lane * 4]);
    float m = -INFINITY, l = 0.f, a0 = 0.f, a1 = 0.f, a2 = 0.f, a3 = 0.f;
    for (int k = 0; k < SK / FB_SPLIT; k++) {
        const uint2 kv = *reinterpret_cast<const uint2*>(kc + base + (size_t)k * DH);
        const uint2 vv = *reinterpret_cast<const uint2*>(vc + base + (size_t)k * DH);
        float s = q.x * bf_lo(kv.x) + q.y * bf_hi(kv.x) + q.z * bf_lo(kv.y) + q.w * bf_hi(kv.y);
        for (int o = 16; o > 0; o >>= 1) s += __shfl_xor_sync(0xffffffffu, s, o);
        s *= 0.08838834764831845f;
        const float mn = fmaxf(m, s), al = __expf(m - mn), pw = __expf(s - mn);
        m = mn;
        l = l * al + pw;
        a0 = a0 * al + pw * bf_lo(vv.x); a1 = a1 * al + pw * bf_hi(vv.x);
        a2 = a2 * al + pw * bf_lo(vv.y); a3 = a3 * al + pw * bf_hi(vv.y);
    }
    float* dst = fb_part[hq][sp];
    dst[lane * 4] = a0; dst[lane * 4 + 1] = a1; dst[lane * 4 + 2] = a2; dst[lane * 4 + 3] = a3;
    if (lane == 0) { dst[DH] = m; dst[DH + 1] = l; }
}
__global__ void fb_combine_kernel() {
    const int hq = blockIdx.x, d = threadIdx.x;
    float M = -INFINITY, L = 0.f, a = 0.f;
    for (int s = 0; s < FB_SPLIT; s++) M = fmaxf(M, fb_part[hq][s][DH]);
    for (int s = 0; s < FB_SPLIT; s++) {
        const float w = __expf(fb_part[hq][s][DH] - M);
        L += w * fb_part[hq][s][DH + 1];
        a += w * fb_part[hq][s][d];
    }
    fb_o[hq * DH + d] = __bfloat162float(__float2bfloat16(a / L));
}
__global__ void fb_out_kernel(const __nv_bfloat16* __restrict__ wo, __nv_bfloat16* __restrict__ out) {
    const int c = blockIdx.x * blockDim.x + threadIdx.x;
    float a = 0.f;
    for (int i = 0; i < QCOLS; i++) a = fmaf(fb_o[i], __bfloat162float(wo[(size_t)i * D_MODEL + c]), a);
    out[c] = __float2bfloat16(a);
}

}

extern "C" void kernel_launch(void* const* d_in, const int* in_sizes, int n_in, void* d_out, int out_size) {
    (void)in_sizes; (void)n_in; (void)out_size;
    const __nv_bfloat16* x = (const __nv_bfloat16*)d_in[0];
    const __nv_bfloat16* kc = (const __nv_bfloat16*)d_in[1];
    const __nv_bfloat16* vc = (const __nv_bfloat16*)d_in[2];
    const __nv_bfloat16* wq = (const __nv_bfloat16*)d_in[3];
    const __nv_bfloat16* wo = (const __nv_bfloat16*)d_in[4];
    __nv_bfloat16* out = (__nv_bfloat16*)d_out;
    cudaStream_t stream = cudaStreamPerThread;

    cudaLaunchConfig_t cfg = {};
    cudaLaunchAttribute at[1];
    at[0].id = cudaLaunchAttributeClusterDimension;
    at[0].val.clusterDim.x = CL;
    at[0].val.clusterDim.y = 1;
    at[0].val.clusterDim.z = 1;
    cfg.attrs = at;
    cfg.numAttrs = 1;
    cfg.blockDim = dim3(NTHREADS);
    cfg.dynamicSmemBytes = SM_TOTAL;
    cfg.stream = stream;

    static int ncl = 0;
    static Scratch* scratch = nullptr;
    static CUtensorMap wo_map48;
    static const void* wo_mapped = nullptr;
    static bool maps_ok = false;
    if (ncl == 0) {
        int n = 0;
        cfg.gridDim = dim3(MAX_CL * CL);
        if (cudaFuncSetAttribute(gqa_decode_kernel<1>, cudaFuncAttributeMaxDynamicSharedMemorySize, SM_TOTAL) != cudaSuccess ||
            cudaFuncSetAttribute(gqa_decode_kernel<2>, cudaFuncAttributeMaxDynamicSharedMemorySize, SM_TOTAL) != cudaSuccess ||
            cudaGetSymbolAddress((void**)&scratch, g_scratch) != cudaSuccess ||
            cudaOccupancyMaxActiveClusters(&n, gqa_decode_kernel<1>, &cfg) != cudaSuccess) {
            (void)cudaGetLastError();
            n = 0;
        }
        ncl = n > MAX_CL ? MAX_CL : (n < MIN_CL ? -1 : n);
    }
    if (wo_mapped != (const void*)wo) {
        typedef CUresult (*EncodeFn)(CUtensorMap*, CUtensorMapDataType, cuuint32_t, void*, const cuuint64_t*,
                                     const cuuint64_t*, const cuuint32_t*, const cuuint32_t*, CUtensorMapInterleave,
                                     CUtensorMapSwizzle, CUtensorMapL2promotion, CUtensorMapFloatOOBfill);
        void* fn = nullptr;
        cudaDriverEntryPointQueryResult st;
        maps_ok = cudaGetDriverEntryPoint("cuTensorMapEncodeTiled", &fn, cudaEnableDefault, &st) == cudaSuccess && fn;
        const cuuint64_t gdim[2] = {(cuuint64_t)D_MODEL, (cuuint64_t)QCOLS};
        const cuuint64_t gstr[1] = {(cuuint64_t)D_MODEL * 2};
        const cuuint32_t box48[2] = {48, 256}, estr[2] = {1, 1};
        if (maps_ok)
            maps_ok = ((EncodeFn)fn)(&wo_map48, CU_TENSOR_MAP_DATA_TYPE_BFLOAT16, 2, d_in[4], gdim, gstr, box48, estr,
                                     CU_TENSOR_MAP_INTERLEAVE_NONE, CU_TENSOR_MAP_SWIZZLE_NONE,
                                     CU_TENSOR_MAP_L2_PROMOTION_L2_128B, CU_TENSOR_MAP_FLOAT_OOB_FILL_NONE) == CUDA_SUCCESS;
        wo_mapped = (const void*)wo;
    }
    if (ncl > 0 && maps_ok) {
        cfg.gridDim = dim3(ncl * CL);
        cudaLaunchKernelEx(&cfg, ncl >= 15 ? gqa_decode_kernel<1> : gqa_decode_kernel<2>, ncl, 0u, kc, vc, wq, x, scratch, wo,
                           out, wo_map48);
    } else {
        fb_q_kernel<<<QCOLS / 128, 128, 0, stream>>>(x, wq);
        fb_attn_kernel<<<dim3(FB_SPLIT, HKV), 64, 0, stream>>>(kc, vc);
        fb_combine_kernel<<<HQ, DH, 0, stream>>>();
        fb_out_kernel<<<D_MODEL / 64, 64, 0, stream>>>(wo, out);
    }
}
```

```cpp
#include <cuda_runtime.h>
#include <cuda.h>
#include <cuda_bf16.h>
#include <stdint.h>

namespace {

constexpr int D_MODEL = 576;
constexpr int HQ = 32;
constexpr int HKV = 16;
constexpr int SK = 65536;
constexpr int DH = 128;
constexpr int QCOLS = HQ * DH;

constexpr int TILE_KEYS = 64;
constexpr int TILE_BYTES = TILE_KEYS * DH * 2;
constexpr int TILES_PER_HEAD = SK / TILE_KEYS;
constexpr int NTILES = TILES_PER_HEAD * HKV;
constexpr int STAGES = 6;

constexpr int PACE = 100;
constexpr int GAP0 = 43;
constexpr int GAP_UP = 3, GAP_DN = 4;
constexpr int WIN_K = 4, WIN_V = 3;

constexpr int CL = 8;
constexpr int NSR = 5;
constexpr int NAR = CL - NSR;
constexpr int MAX_CL = 16, MIN_CL = 12;
constexpr int NPAIR = 3;
constexpr int NCONS = 2 * NPAIR;
constexpr int NTHREADS = 8 * 32;
static_assert(NCONS + 2 == NTHREADS / 32, "warp roles");
constexpr int NQITEM = QCOLS / 64;
constexpr int QROWS = D_MODEL / NAR;
constexpr int QLEAD = 2;
constexpr int NOWN = D_MODEL / 16;
constexpr int NSLOT = NSR * NCONS;
constexpr uint32_t MERGE_BYTES = NSLOT * 1024, ML_BYTES = NSLOT * 16;

constexpr int SS_STAGE = 0;
constexpr int STAGE_BYTES = 2 * TILE_BYTES;
constexpr int SS_Q = SS_STAGE + STAGES * STAGE_BYTES;
constexpr int DEFK = 3;
constexpr int DEF = DEFK * NSR;
static_assert(DEF == HKV - 1 && DEFK <= NPAIR, "all heads but the last are projected late");
constexpr int SS_O = SS_Q + QCOLS * 2;
constexpr int SS_BAR = SS_O + 3 * 512;
constexpr int SS_BARO = SS_BAR + (3 * STAGES + HKV + NAR) * 8;
constexpr int METAS = 16;
constexpr int SS_META = SS_BARO + 3 * 8;
constexpr int SS_TOTAL = SS_META + METAS * 4;
constexpr int WO_BOX = 256 * 96;
constexpr int SA_WO = 0;
constexpr int SA_SLOT = SA_WO + 4 * WO_BOX;
constexpr int SA_ML = SA_SLOT + NSLOT * 1024;
constexpr int SA_BAR = SA_ML + 2 * NSLOT * 8;
constexpr int SA_BARML = SA_BAR + 8;
constexpr int INBOX = SA_BARML + 8 - SA_SLOT;
constexpr int SA_QRED = SA_SLOT + 2 * INBOX;
constexpr int SA_O = SA_QRED + QLEAD * NAR * 8 * 256;
constexpr int LATE_N = 12;
constexpr int SA_ORED = SA_O + 512;
constexpr int SA_WT = SA_ORED + 16 * LATE_N * 4;
constexpr int SA_LSE = SA_WT + 4 * 32 * 4;
constexpr int SA_FL = SA_LSE + 128;
constexpr int SA_BARDEF = SA_FL + 256;
constexpr int SA_BARWO = SA_BARDEF + 8;
constexpr int SA_BARQ = SA_BARWO + 8;
constexpr int SA_BARGO = SA_BARQ + QLEAD * 8;
constexpr int SA_TOTAL = SA_BARGO + 5 * 8;
static_assert(INBOX % 16 == 0 && SA_SLOT % 16 == 0, "alignment");
constexpr int SM_TOTAL = SS_TOTAL > SA_TOTAL ? SS_TOTAL : SA_TOTAL;

constexpr uint32_t SPIN_LIMIT = 1u << 22;

struct Scratch {
    float2 part[HKV - 1][MAX_CL][128];
    uint4 flag[HKV - 1][MAX_CL][2];
    uint4 ypk[NOWN][MAX_CL][16];
    unsigned long long qpk[QCOLS / 2];
    unsigned int epoch;
    unsigned int pad0[31];
    unsigned int ticket;
    unsigned int pad1[31];
};
__device__ __align__(128) Scratch g_scratch;

__device__ __forceinline__ uint32_t smem_u32(const void* p) { return (uint32_t)__cvta_generic_to_shared(p); }
__device__ __forceinline__ uint32_t pin(uint32_t v) {
    asm volatile("mov.b32 %0, %0;" : "+r"(v));
    return v;
}
__device__ __forceinline__ uint32_t hold(uint32_t v) { return __shfl_sync(0xffffffffu, v, threadIdx.x & 31); }
template <typename T>
__device__ __forceinline__ T* hold(T* p) {
    return reinterpret_cast<T*>(__shfl_sync(0xffffffffu, reinterpret_cast<unsigned long long>(p), threadIdx.x & 31));
}
__device__ __forceinline__ uint32_t mapa(uint32_t a, uint32_t rank) {
    uint32_t r;
    asm("mapa.shared::cluster.u32 %0, %1, %2;" : "=r"(r) : "r"(a), "r"(rank));
    return r;
}
__device__ __forceinline__ void mbar_init(uint32_t bar, uint32_t cnt) {
    asm volatile("mbarrier.init.shared::cta.b64 [%0], %1;" ::"r"(bar), "r"(cnt) : "memory");
}
__device__ __forceinline__ void mbar_expect_tx(uint32_t bar, uint32_t bytes) {
    asm volatile("mbarrier.arrive.expect_tx.shared::cta.b64 _, [%0], %1;" ::"r"(bar), "r"(bytes) : "memory");
}
__device__ __forceinline__ void mbar_arrive(uint32_t bar) {
    asm volatile("mbarrier.arrive.shared::cta.b64 _, [%0];" ::"r"(bar) : "memory");
}
__device__ __forceinline__ bool mbar_try_for(uint32_t bar, uint32_t parity, uint32_t ns) {
    uint32_t ok;
    asm volatile(
        "{\n.reg .pred p;\nmbarrier.try_wait.parity.shared::cta.b64 p, [%1], %2, %3;\nselp.u32 %0, 1, 0, p;\n}"
        : "=r"(ok) : "r"(bar), "r"(parity), "r"(ns) : "memory");
    return ok != 0;
}
__device__ __forceinline__ bool mbar_test(uint32_t bar, uint32_t parity) {
    uint32_t ok;
    asm volatile(
        "{\n.reg .pred p;\nmbarrier.test_wait.parity.shared::cta.b64 p, [%1], %2;\nselp.u32 %0, 1, 0, p;\n}"
        : "=r"(ok) : "r"(bar), "r"(parity) : "memory");
    return ok != 0;
}
__device__ __forceinline__ void mbar_wait(uint32_t bar, uint32_t parity) {
    uint32_t n = 0;
    while (!mbar_try_for(bar, parity, 1000)) {
        if (++n > SPIN_LIMIT) __trap();
    }
}
__device__ __forceinline__ void cluster_arrive_relaxed() { asm volatile("barrier.cluster.arrive.relaxed.aligned;" ::: "memory"); }
__device__ __forceinline__ void cluster_wait() { asm volatile("barrier.cluster.wait.acquire.aligned;" ::: "memory"); }
__device__ __forceinline__ void st_async_v4(uint32_t caddr, float a, float b, float c, float d, uint32_t cbar) {
    asm volatile("st.async.weak.shared::cluster.mbarrier::complete_tx::bytes.v4.f32 [%0], {%1,%2,%3,%4}, [%5];"
                 ::"r"(caddr), "f"(a), "f"(b), "f"(c), "f"(d), "r"(cbar) : "memory");
}
__device__ __forceinline__ void st_async_v2(uint32_t caddr, uint32_t a, uint32_t b, uint32_t cbar) {
    asm volatile("st.async.weak.shared::cluster.mbarrier::complete_tx::bytes.v2.b32 [%0], {%1,%2}, [%3];"
                 ::"r"(caddr), "r"(a), "r"(b), "r"(cbar) : "memory");
}
__device__ __forceinline__ void st_async_b32(uint32_t caddr, uint32_t a, uint32_t cbar) {
    asm volatile("st.async.weak.shared::cluster.mbarrier::complete_tx::bytes.b32 [%0], %1, [%2];"
                 ::"r"(caddr), "r"(a), "r"(cbar) : "memory");
}
__device__ __forceinline__ void bulk_load(uint32_t dst, const void* src, uint32_t bytes, uint32_t bar, uint64_t pol) {
    asm volatile(
        "cp.async.bulk.shared::cluster.global.mbarrier::complete_tx::bytes.L2::cache_hint [%0], [%1], %2, [%3], %4;"
        ::"r"(dst), "l"(src), "r"(bytes), "r"(bar), "l"(pol) : "memory");
}
__device__ __forceinline__ void l2_prefetch(const void* src, uint32_t bytes) {
    asm volatile("cp.async.bulk.prefetch.L2.global [%0], %1;" ::"l"(src), "r"(bytes) : "memory");
}
__device__ __forceinline__ void tma_load_2d(uint32_t dst, const CUtensorMap* tm, int c0, int c1, uint32_t bar) {
    asm volatile("cp.async.bulk.tensor.2d.shared::cluster.global.mbarrier::complete_tx::bytes [%0], [%1, {%3, %4}], [%2];"
                 ::"r"(dst), "l"(tm), "r"(bar), "r"(c0), "r"(c1) : "memory");
}
__device__ __forceinline__ uint4 lds128(uint32_t a) {
    uint4 v;
    asm volatile("ld.shared.v4.u32 {%0,%1,%2,%3}, [%4];" : "=r"(v.x), "=r"(v.y), "=r"(v.z), "=r"(v.w) : "r"(a) : "memory");
    return v;
}
__device__ __forceinline__ uint32_t lds32(uint32_t a) {
    uint32_t v;
    asm volatile("ld.shared.b32 %0, [%1];" : "=r"(v) : "r"(a) : "memory");
    return v;
}
__device__ __forceinline__ float2 lds64f(uint32_t a) {
    float2 v;
    asm volatile("ld.shared.v2.f32 {%0,%1}, [%2];" : "=f"(v.x), "=f"(v.y) : "r"(a) : "memory");
    return v;
}
__device__ __forceinline__ void sts32(uint32_t a, uint32_t v) { asm volatile("st.shared.b32 [%0], %1;" ::"r"(a), "r"(v) : "memory"); }
__device__ __forceinline__ float4 lds128f(uint32_t a) {
    float4 v;
    asm volatile("ld.shared.v4.f32 {%0,%1,%2,%3}, [%4];" : "=f"(v.x), "=f"(v.y), "=f"(v.z), "=f"(v.w) : "r"(a) : "memory");
    return v;
}
__device__ __forceinline__ uint4 ldsm_x4_trans(uint32_t a) {
    uint4 v;
    asm volatile("ldmatrix.sync.aligned.m8n8.x4.trans.shared.b16 {%0,%1,%2,%3}, [%4];"
                 : "=r"(v.x), "=r"(v.y), "=r"(v.z), "=r"(v.w) : "r"(a) : "memory");
    return v;
}
__device__ __forceinline__ void mma_bf16(float (&c)[4], uint32_t a0, uint32_t a1, uint32_t a2, uint32_t a3,
                                         uint32_t b0, uint32_t b1) {
    asm volatile(
        "mma.sync.aligned.m16n8k16.row.col.f32.bf16.bf16.f32 {%0,%1,%2,%3}, {%4,%5,%6,%7}, {%8,%9}, {%0,%1,%2,%3};"
        : "+f"(c[0]), "+f"(c[1]), "+f"(c[2]), "+f"(c[3])
        : "r"(a0), "r"(a1), "r"(a2), "r"(a3), "r"(b0), "r"(b1));
}
__device__ __forceinline__ uint4 ldg_nc128(const void* p) {
    uint4 v;
    asm volatile("ld.global.nc.L1::no_allocate.L2::128B.v4.u32 {%0,%1,%2,%3}, [%4];"
                 : "=r"(v.x), "=r"(v.y), "=r"(v.z), "=r"(v.w) : "l"(p));
    return v;
}
__device__ __forceinline__ int draw_ticket(unsigned int* counter) {
    int v;
    asm volatile("atom.relaxed.gpu.global.inc.u32 %0, [%1], 0x7fffffff;" : "=r"(v) : "l"(counter) : "memory");
    return v;
}
__device__ __forceinline__ uint32_t ld_relaxed32(const void* p) {
    uint32_t v;
    asm volatile("ld.relaxed.gpu.global.b32 %0, [%1];" : "=r"(v) : "l"(p) : "memory");
    return v;
}
__device__ __forceinline__ unsigned long long ld_relaxed64(const void* p) {
    unsigned long long v;
    asm volatile("ld.relaxed.gpu.global.b64 %0, [%1];" : "=l"(v) : "l"(p) : "memory");
    return v;
}
__device__ __forceinline__ void st_relaxed64(void* p, unsigned long long v) {
    asm volatile("st.relaxed.gpu.global.b64 [%0], %1;" ::"l"(p), "l"(v) : "memory");
}
__device__ __forceinline__ void ld_relaxed64x2(const void* p, unsigned long long& lo, unsigned long long& hi) {
    asm volatile("ld.relaxed.gpu.global.v2.b64 {%0, %1}, [%2];" : "=l"(lo), "=l"(hi) : "l"(p) : "memory");
}
__device__ __forceinline__ void ld_relaxed128(const void* p, unsigned long long& lo, unsigned long long& hi) {
    asm volatile("{\n.reg .b128 t;\nld.relaxed.gpu.global.b128 t, [%2];\nmov.b128 {%0, %1}, t;\n}"
                 : "=l"(lo), "=l"(hi) : "l"(p) : "memory");
}
__device__ __forceinline__ void ld_acquire128(const void* p, unsigned long long& lo, unsigned long long& hi) {
    asm volatile("{\n.reg .b128 t;\nld.acquire.gpu.global.b128 t, [%2];\nmov.b128 {%0, %1}, t;\n}"
                 : "=l"(lo), "=l"(hi) : "l"(p) : "memory");
}
__device__ __forceinline__ void st_relaxed128(void* p, unsigned long long lo, unsigned long long hi) {
    asm volatile("{\n.reg .b128 t;\nmov.b128 t, {%1, %2};\nst.relaxed.gpu.global.b128 [%0], t;\n}"
                 ::"l"(p), "l"(lo), "l"(hi) : "memory");
}
__device__ __forceinline__ float ex2(float x) {
    float y;
    asm("ex2.approx.ftz.f32 %0, %1;" : "=f"(y) : "f"(x));
    return y;
}
__device__ __forceinline__ float rcp(float x) {
    float y;
    asm("rcp.approx.ftz.f32 %0, %1;" : "=f"(y) : "f"(x));
    return y;
}
__device__ __forceinline__ float warp_max(float v) {
    int k = __float_as_int(v);
    k ^= (k >> 31) & 0x7fffffff;
    k = __reduce_max_sync(0xffffffffu, k);
    k ^= (k >> 31) & 0x7fffffff;
    return __int_as_float(k);
}
__device__ __forceinline__ uint32_t pack_bf16(float lo, float hi) {
    uint32_t r;
    asm("cvt.rn.bf16x2.f32 %0, %1, %2;" : "=r"(r) : "f"(hi), "f"(lo));
    return r;
}
__device__ __forceinline__ float bf_lo(uint32_t v) { return __uint_as_float(v << 16); }
__device__ __forceinline__ float bf_hi(uint32_t v) { return __uint_as_float(v & 0xffff0000u); }
__device__ __forceinline__ void named_sync(int id, int n) { asm volatile("bar.sync %0, %1;" ::"r"(id), "r"(n) : "memory"); }
__device__ __forceinline__ void fma8(float* a, float s, const uint4& w) {
    a[0] = fmaf(s, bf_lo(w.x), a[0]); a[1] = fmaf(s, bf_hi(w.x), a[1]);
    a[2] = fmaf(s, bf_lo(w.y), a[2]); a[3] = fmaf(s, bf_hi(w.y), a[3]);
    a[4] = fmaf(s, bf_lo(w.z), a[4]); a[5] = fmaf(s, bf_hi(w.z), a[5]);
    a[6] = fmaf(s, bf_lo(w.w), a[6]); a[7] = fmaf(s, bf_hi(w.w), a[7]);
}

__global__ void __cluster_dims__(CL, 1, 1) __launch_bounds__(NTHREADS, 1)
gqa_decode_kernel(int ncl, uint32_t zero, const __nv_bfloat16* __restrict__ kc, const __nv_bfloat16* __restrict__ vc,
                  const __nv_bfloat16* __restrict__ wq, const __nv_bfloat16* __restrict__ x, Scratch* __restrict__ sc,
                  const __nv_bfloat16* __restrict__ wo, __nv_bfloat16* __restrict__ out,
                  const __grid_constant__ CUtensorMap wo_map48) {
    extern __shared__ __align__(1024) unsigned char smem[];
    const uint32_t sb = smem_u32(smem);
    const int tid = threadIdx.x, warp = tid >> 5, lane = tid & 31;
    const int rank = blockIdx.x % CL, cl = blockIdx.x / CL;
    constexpr float SCL = 0.08838834764831845f * 1.4426950408889634f;

    if (rank < NSR) {
        const uint32_t bar_full = sb + SS_BAR, bar_empty = bar_full + STAGES * 8;
        const uint32_t bar_q = bar_empty + STAGES * 8, bar_free = bar_q + HKV * 8, bar_fk = bar_free + NAR * 8;
        volatile uint32_t* meta = reinterpret_cast<volatile uint32_t*>(smem + SS_META);
        if (warp == NCONS + 1) {
            const uint32_t tag = ld_relaxed32(&sc->epoch) + 1u;
            if (lane == 0) {
#pragma unroll
                for (int a = 0; a < NAR; a++) mbar_init(bar_free + a * 8, 1);
#pragma unroll
                for (int k = 0; k < DEFK; k++) mbar_init(sb + SS_BARO + k * 8, 1);
                asm volatile("fence.mbarrier_init.release.cluster;" ::: "memory");
            }
            __syncwarp();
            cluster_arrive_relaxed();
            if (lane == 0) {
#pragma unroll
                for (int h = 0; h < HKV; h++) mbar_init(bar_q + h * 8, 32);
#pragma unroll
                for (int k = 0; k < DEFK; k++) mbar_expect_tx(sb + SS_BARO + k * 8, 512);
            }
            __syncwarp();
            asm volatile("bar.arrive 1, %0;" ::"n"((NCONS + 2) * 32) : "memory");
#pragma unroll 1
            for (int h = 0; h < HKV; h++) {
                if (h == 1) __nanosleep(1500);
                if (h == ncl / 4) __nanosleep(8000);
                unsigned long long lo[2], hi[2];
                uint32_t n = 0;
                while (true) {
                    bool ok = true;
#pragma unroll
                    for (int k = 0; k < 2; k++) {
                        ld_relaxed64x2(&sc->qpk[h * 128 + (k * 32 + lane) * 2], lo[k], hi[k]);
                        ok = ok && ((uint32_t)(lo[k] >> 32) == tag) && ((uint32_t)(hi[k] >> 32) == tag);
                    }
                    if (ok) break;
                    if (h > 0) __nanosleep(500);
                    if (++n > SPIN_LIMIT) __trap();
                }
#pragma unroll
                for (int k = 0; k < 2; k++)
                    *reinterpret_cast<uint2*>(smem + SS_Q + h * 512 + (k * 32 + lane) * 8) = make_uint2((uint32_t)lo[k], (uint32_t)hi[k]);
                mbar_arrive(bar_q + h * 8);
            }
            return;
        }
        if (warp == NCONS) {
            const int ns = ncl * NSR, sid = cl * NSR + rank;
            const int pace = PACE * ncl;
            uint64_t pol = 0;
            const char* kp = reinterpret_cast<const char*>(kc);
            const char* vp = reinterpret_cast<const char*>(vc);
            auto issue_k = [&](int i, int s, int t) {
                mbar_expect_tx(bar_fk + s * 8, TILE_BYTES);
                bulk_load(sb + SS_STAGE + s * STAGE_BYTES, kp + (size_t)t * TILE_BYTES, TILE_BYTES, bar_fk + s * 8, pol);
                meta[(i + 1) % METAS] = ((uint32_t)(i + 1) << 5) | (uint32_t)(t / TILES_PER_HEAD);
            };
            auto issue_v = [&](int s, int t) {
                mbar_expect_tx(bar_full + s * 8, TILE_BYTES);
                bulk_load(sb + SS_STAGE + s * STAGE_BYTES + TILE_BYTES, vp + (size_t)t * TILE_BYTES, TILE_BYTES, bar_full + s * 8, pol);
            };
            auto issue = [&](int i, int s, int t) { issue_k(i, s, t); issue_v(s, t); };
            if (lane < METAS) meta[lane] = 0;
            __syncwarp();
            long long t_start = 0;
            if (lane == 0) {
#pragma unroll
                for (int s = 0; s < STAGES; s++) {
                    mbar_init(bar_full + s * 8, 1);
                    mbar_init(bar_fk + s * 8, 1);
                    mbar_init(bar_empty + s * 8, 2);
                }
                asm volatile("fence.proxy.async.shared::cta;" ::: "memory");
                asm volatile("createpolicy.fractional.L2::evict_first.b64 %0, 1.0;" : "=l"(pol));
                t_start = clock64();
                issue(0, 0, sid);
            }
            __syncwarp();
            asm volatile("bar.arrive 1, %0;" ::"n"((NCONS + 2) * 32) : "memory");
            if (lane != 0) return;
            asm volatile("barrier.cluster.arrive.relaxed;" ::: "memory");
#pragma unroll 1
            for (int s = 1; s < STAGES; s++) {
                while (clock64() - t_start < (long long)(s * pace)) { }
                issue(s, s, sid + s * ns);
            }
            const int base = (STAGES + 1) * ns;
            int tk = sid + STAGES * ns - base, tprev = -1;
            int i = STAGES, s = 0;
            uint32_t ph = 1;
            auto back = [&](int d) { return (uint32_t)(s < d ? s - d + STAGES : s - d) * 8; };
            auto bpar = [&](int d) { return s < d ? ph ^ 1 : ph; };
            int gap = GAP0 * ncl;
            uint32_t t_next = (uint32_t)clock64();
            auto meter = [&]() {
                uint32_t now = (uint32_t)clock64();
                if ((int)(t_next - now) > 250) __nanosleep((t_next - now - 250) / 2);
                do { now = (uint32_t)clock64(); } while ((int)(now - t_next) < 0);
                t_next = ((int)(now - t_next) < 40) ? t_next + gap : now + gap - 40;
            };
            while (true) {
                const int t = tk + base;
                if (t < NTILES) {
                    mbar_wait(bar_empty + s * 8, ph ^ 1);
                    mbar_wait(bar_fk + back(WIN_K), bpar(WIN_K));
                    meter();
                    if (i >= STAGES + 4) gap = max(gap + (mbar_test(bar_fk + back(2), bpar(2)) ? -GAP_DN : GAP_UP), 0);
                    tk = draw_ticket(&sc->ticket);
                    issue_k(i, s, t);
                } else {
#pragma unroll
                    for (int k = 0; k < NPAIR; k++) meta[(i + 1 + k) % METAS] = ((uint32_t)(i + 1 + k) << 5) | (uint32_t)(HKV + k);
                    asm volatile("prefetch.tensormap [%0];" ::"l"(&wo_map48) : "memory");
                }
                if (tprev >= 0) {
                    mbar_wait(bar_full + back(WIN_V + 1), bpar(WIN_V + 1));
                    meter();
                    issue_v(back(1) / 8, tprev);
                }
                if (t >= NTILES) break;
                tprev = t;
                i++;
                if (++s == STAGES) { s = 0; ph ^= 1; }
            }
            if (cl < NOWN / NAR) {
                const uint32_t t_end = (uint32_t)clock64();
                mbar_wait(bar_fk + back(4), bpar(4));
#pragma unroll
                for (int k = 0; k < DEFK; k++) {
                    const uint32_t due = t_end + (uint32_t)(gap * (8 + 5 * k) / 4);
                    while ((int)((uint32_t)clock64() - due) < 0) { }
                    mbar_wait(bar_empty + s * 8, ph ^ 1);
                    mbar_expect_tx(bar_fk + s * 8, WO_BOX);
                    tma_load_2d(sb + SS_STAGE + s * STAGE_BYTES, &wo_map48, cl * 48, (k * NSR + rank) * 256, bar_fk + s * 8);
                    if (++s == STAGES) { s = 0; ph ^= 1; }
                }
            }
            return;
        }
        cluster_arrive_relaxed();
        const int g = lane >> 2, t4 = lane & 3;
        const uint32_t koff = ((warp & 1) * 32 + g) * 256 + t4 * 16 + (g & 1) * 64;
        const uint32_t qoff = (g >> 2) * 256 + t4 * 16 + (((g >> 1) ^ g) & 1) * 64;
        const int kk = lane & 7, mi = lane >> 3;
        const uint32_t voff = TILE_BYTES + ((warp & 1) * 32 + 2 * (kk >> 1) + (mi >> 1) + 8 * (kk & 1)) * 256 +
                              ((mi ^ kk) & 1) * 16 + (kk >> 1) * 32;
        const int slot = rank * NCONS + warp;
        const uint32_t ka0 = pin(sb + SS_STAGE + koff), ka1 = pin(sb + SS_STAGE + (koff ^ 64));
        const uint32_t va0 = pin(sb + SS_STAGE + voff), va1 = pin(sb + SS_STAGE + (voff ^ 32));
        const uint32_t va2 = pin(sb + SS_STAGE + (voff ^ 64)), va3 = pin(sb + SS_STAGE + (voff ^ 96));
        const uint32_t bars = pin(bar_full), metas = pin(sb + SS_META);
        const uint32_t src0 = pin(8 * t4 + 2 * (g >> 2));
        const uint32_t bmask = pin(t4 == (g & 3) ? 0xffffffffu : 0u);
        const uint32_t oddm = pin((g ^ t4) & 1);
        const uint32_t zr = pin(zero), ln = pin(lane);
        const uint32_t poff = pin(SA_SLOT + slot * 1024 + (t4 >> 1) * 512 + (g * 2 + (t4 & 1)) * 16);
        const uint32_t poffb = pin(SA_SLOT + slot * 512 + (t4 >> 1) * 256 + (g * 2 + (t4 & 1)) * 16);
        const uint32_t mloff = pin((g == 0 && (t4 & 1) == 0) ? SA_ML + ((t4 >> 1) * NSLOT + slot) * 8 : 0);
        named_sync(1, (NCONS + 2) * 32);

        constexpr uint32_t FK = (2 * STAGES + HKV + NAR) * 8, EM = STAGES * 8;
        static_assert(STAGES % NPAIR == 0 && NSLOT <= 32, "a warp pair owns every NPAIR-th stage");
        int s = warp >> 1;
        uint32_t ph = 0, seq = 1 + (warp >> 1);
        int th = 0;
#pragma unroll 1
        for (int h = 0; h < HKV; h++) {
            mbar_wait(bar_q + h * 8, 0);
            uint4 qf[4];
#pragma unroll
            for (int j = 0; j < 4; j++) qf[j] = lds128(sb + SS_Q + h * 512 + (qoff ^ (j * 64)));
            float acc[8][4];
#pragma unroll
            for (int i = 0; i < 8; i++) { acc[i][0] = acc[i][1] = acc[i][2] = acc[i][3] = 0.f; }
            float m = -INFINITY, l = 0.f, lsum = 0.f;
            bool ml_sent = false;
            if (h == 0) cluster_wait();
            const bool last = (h == HKV - 1);
            if (h >= NAR && !last) mbar_wait(bar_free + (h % NAR) * 8, (uint32_t)(h / NAR - 1) & 1u);
            const uint32_t rb_ = pin(mapa(sb, NSR + h % NAR) + (last ? INBOX : 0));
            const uint32_t rb1 = pin(last ? mapa(sb, NSR + 1) + INBOX : 0u), rb2 = pin(mapa(sb, NSR + 2) + INBOX);
            auto send_ml = [&]() {
                if (mloff) {
                    st_async_v2(rb_ + mloff, __float_as_uint(m), __float_as_uint(lsum), rb_ + SA_BARML);
                    if (rb1) {
                        st_async_v2(rb1 + mloff, __float_as_uint(m), __float_as_uint(lsum), rb1 + SA_BARML);
                        st_async_v2(rb2 + mloff, __float_as_uint(m), __float_as_uint(lsum), rb2 + SA_BARML);
                    }
                }
            };
            while (th == h) {
                const uint32_t so = s * STAGE_BYTES, bv = bars + s * 8, pvh = ph;
                float sc[4];
                {
                    const uint32_t a0 = ka0 + so, a1 = ka1 + so;
                    mbar_wait(bv + FK, pvh);
#pragma unroll
                    for (int u = 0; u < 2; u++) {
                        uint4 ra[4], rb[4];
                        ra[0] = lds128(a0 + u * 4096); rb[0] = lds128(a0 + u * 4096 + 2048);
                        ra[1] = lds128(a1 + u * 4096); rb[1] = lds128(a1 + u * 4096 + 2048);
                        ra[2] = lds128(a0 + u * 4096 + 128); rb[2] = lds128(a0 + u * 4096 + 2048 + 128);
                        ra[3] = lds128(a1 + u * 4096 + 128); rb[3] = lds128(a1 + u * 4096 + 2048 + 128);
                        float c0[4] = {0.f, 0.f, 0.f, 0.f}, c1[4] = {0.f, 0.f, 0.f, 0.f};
#pragma unroll
                        for (int j = 0; j < 4; j++) {
                            mma_bf16(c0, ra[j].x, rb[j].x, ra[j].y, rb[j].y, qf[j].x, qf[j].y);
                            mma_bf16(c1, ra[j].z, rb[j].z, ra[j].w, rb[j].w, qf[j].z, qf[j].w);
                        }
                        sc[2 * u] = oddm ? (c0[1] + c1[1]) : (c0[0] + c1[0]);
                        sc[2 * u + 1] = oddm ? (c0[3] + c1[3]) : (c0[2] + c1[2]);
                    }
                }
                float mx = fmaxf(fmaxf(sc[0], sc[1]), fmaxf(sc[2], sc[3]));
                mx = fmaxf(mx, __shfl_xor_sync(0xffffffffu, mx, 4));
                mx = fmaxf(mx, __shfl_xor_sync(0xffffffffu, mx, 8));
                mx = fmaxf(mx, __shfl_xor_sync(0xffffffffu, mx, 16));
                const float mn = fmaxf(m, mx);
                const float alpha = ex2((m - mn) * SCL);
                const float p0 = ex2((sc[0] - mn) * SCL), p1 = ex2((sc[1] - mn) * SCL);
                const float p2 = ex2((sc[2] - mn) * SCL), p3 = ex2((sc[3] - mn) * SCL);
                m = mn;
                l = fmaf(l, alpha, (p0 + p1) + (p2 + p3));
                const uint32_t pka = pack_bf16(p0, p1), pkb = pack_bf16(p2, p3);
                uint32_t bf[4];
                bf[0] = __shfl_sync(0xffffffffu, pka, src0) & bmask;
                bf[1] = __shfl_sync(0xffffffffu, pka, src0 + 4) & bmask;
                bf[2] = __shfl_sync(0xffffffffu, pkb, src0) & bmask;
                bf[3] = __shfl_sync(0xffffffffu, pkb, src0 + 4) & bmask;
#pragma unroll
                for (int i = 0; i < 8; i++) { acc[i][0] *= alpha; acc[i][1] *= alpha; acc[i][2] *= alpha; acc[i][3] *= alpha; }
                lsum = l + __shfl_xor_sync(0xffffffffu, l, 4);
                lsum += __shfl_xor_sync(0xffffffffu, lsum, 8);
                lsum += __shfl_xor_sync(0xffffffffu, lsum, 16);
                s += NPAIR;
                if (s >= STAGES) { s -= STAGES; ph ^= 1; }
                seq += NPAIR;
                const uint32_t a0 = va0 + so, a1 = va1 + so, a2 = va2 + so, a3 = va3 + so, ma = metas + (seq % METAS) * 4;
                uint32_t mt, dep = 0, n = 0;
                while (true) {
                    asm volatile("ld.volatile.shared.u32 %0, [%1];" : "=r"(mt) : "r"(ma) : "memory");
                    if ((mt >> 5) == seq) {
                        if ((int)(mt & 31u) != h) {
                            send_ml();
                            ml_sent = true;
                        }
                        mbar_wait(bv, pvh);
                        break;
                    }
                    if (mbar_try_for(bv, pvh, 128)) break;
                    if (++n > SPIN_LIMIT) __trap();
                }
                __syncwarp();
#pragma unroll
                for (int u = 0; u < 2; u++) {
                    uint4 va[8];
                    va[0] = ldsm_x4_trans(a0 + u * 4096); va[1] = ldsm_x4_trans(a1 + u * 4096);
                    va[2] = ldsm_x4_trans(a2 + u * 4096); va[3] = ldsm_x4_trans(a3 + u * 4096);
                    va[4] = ldsm_x4_trans(a0 + u * 4096 + 128); va[5] = ldsm_x4_trans(a1 + u * 4096 + 128);
                    va[6] = ldsm_x4_trans(a2 + u * 4096 + 128); va[7] = ldsm_x4_trans(a3 + u * 4096 + 128);
#pragma unroll
                    for (int i = 0; i < 8; i++)
                        mma_bf16(acc[i], __byte_perm(va[i].x, va[i].y, 0x7610), __byte_perm(va[i].y, va[i].x, 0x7610),
                                 __byte_perm(va[i].z, va[i].w, 0x7610), __byte_perm(va[i].w, va[i].z, 0x7610),
                                 bf[2 * u], bf[2 * u + 1]);
                    dep |= (va[0].x | va[1].x) | (va[2].x | va[3].x | va[4].x) | (va[5].x | va[6].x | va[7].x);
                }
                if (ln == 0) mbar_arrive(bv + EM + (dep & zr));
                n = 0;
                while ((mt >> 5) != seq) {
                    if (n) __nanosleep(32);
                    asm volatile("ld.volatile.shared.u32 %0, [%1];" : "=r"(mt) : "r"(ma) : "memory");
                    if (++n > SPIN_LIMIT) __trap();
                }
                th = (int)(mt & 31u);
            }
            if (!ml_sent) send_ml();
            float w[8];
#pragma unroll
            for (int k = 0; k < 4; k++) {
                const int i = (k & 1) | ((k & 2) << 1);
                w[2 * k] = (acc[i][0] + acc[i ^ 1][1]) + __shfl_xor_sync(0xffffffffu, acc[i ^ 2][0] + acc[i ^ 3][1], 1);
                w[2 * k + 1] = (acc[i][2] + acc[i ^ 1][3]) + __shfl_xor_sync(0xffffffffu, acc[i ^ 2][2] + acc[i ^ 3][3], 1);
            }
            if (rb1) {
                const float b0 = __uint_as_float(pack_bf16(w[0], w[1])), b1 = __uint_as_float(pack_bf16(w[2], w[3]));
                const float b2 = __uint_as_float(pack_bf16(w[4], w[5])), b3 = __uint_as_float(pack_bf16(w[6], w[7]));
                st_async_v4(rb_ + poffb, b0, b1, b2, b3, rb_ + SA_BAR);
                st_async_v4(rb1 + poffb, b0, b1, b2, b3, rb1 + SA_BAR);
                st_async_v4(rb2 + poffb, b0, b1, b2, b3, rb2 + SA_BAR);
            } else {
                st_async_v4(rb_ + poff, w[0], w[1], w[2], w[3], rb_ + SA_BAR);
                st_async_v4(rb_ + poff + 256, w[4], w[5], w[6], w[7], rb_ + SA_BAR);
            }
        }
        if (cl < NOWN / NAR) {
            static_assert(NPAIR == NAR && DEFK == NPAIR, "warp pair <-> column owner");
            s -= th - HKV;
            if (s < 0) { s += STAGES; ph ^= 1; }
            const uint32_t bm = (lane & 4) ? 0xffff0000u : 0x0000ffffu;
            uint4 bo[DEFK][4];
#pragma unroll
            for (int k = 0; k < DEFK; k++) {
                mbar_wait(sb + SS_BARO + k * 8, 0);
#pragma unroll
                for (int i = 0; i < 4; i++) {
                    bo[k][i] = lds128(sb + SS_O + k * 512 + ((warp & 1) * 64 + i * 16 + t4 * 4) * 4);
                    bo[k][i].x &= bm; bo[k][i].y &= bm; bo[k][i].z &= bm; bo[k][i].w &= bm;
                }
            }
            const uint32_t ab = hold(sb + SS_STAGE + ((warp & 1) * 128 + (lane >> 4) * 16 + ((lane >> 1) & 3) + (lane & 1) * 8) * 96 +
                                     (warp >> 1) * 32 + (((lane >> 3) ^ lane) & 1) * 16);
            const uint32_t ra = mapa(sb, NSR + (warp >> 1));
            const uint32_t dst = hold(t4 < 2 ? ra + SA_ORED + ((g + t4 * 8) * LATE_N + rank * 2 + (warp & 1)) * 4 : 0u);
            const uint32_t dbar = hold(ra + SA_BARDEF), hi = hold(t4 & 1);
            float d[4][4];
#pragma unroll
            for (int i = 0; i < 4; i++) d[i][0] = d[i][1] = d[i][2] = d[i][3] = 0.f;
#pragma unroll
            for (int k = 0; k < DEFK; k++) {
                const uint32_t box = ab + s * STAGE_BYTES;
                mbar_wait(bars + FK + s * 8, ph);
                uint4 wf[4][2];
#pragma unroll
                for (int i = 0; i < 4; i++)
#pragma unroll
                    for (int c = 0; c < 2; c++) wf[i][c] = ldsm_x4_trans(box + ((i >> 1) * 64 + c * 32 + (i & 1) * 4) * 96);
#pragma unroll
                for (int c = 0; c < 2; c++)
#pragma unroll
                    for (int i = 0; i < 4; i++)
                        mma_bf16(d[i], wf[i][c].x, wf[i][c].y, wf[i][c].z, wf[i][c].w, c ? bo[k][i].z : bo[k][i].x,
                                 c ? bo[k][i].w : bo[k][i].y);
                if (++s == STAGES) { s = 0; ph ^= 1; }
            }
            const float y = hi ? ((d[0][2] + d[1][2]) + (d[2][2] + d[3][2])) + ((d[0][1] + d[1][1]) + (d[2][1] + d[3][1]))
                               : ((d[0][0] + d[1][0]) + (d[2][0] + d[3][0])) + ((d[0][3] + d[1][3]) + (d[2][3] + d[3][3]));
            if (dst) st_async_b32(dst, __float_as_uint(y), dbar);
        }
        return;
    }

    const int ar = rank - NSR, aid = cl * NAR + ar;
    const uint32_t bar_qred = sb + SA_BARQ;
    const uint32_t tag = ld_relaxed32(&sc->epoch) + 1u;
    uint32_t cleared = 0;
    if (aid == 0 && tid == 0)
        asm volatile("atom.relaxed.gpu.global.exch.b32 %0, [%1], 0;" : "=r"(cleared) : "l"(&sc->ticket) : "memory");
    {
        const int row0 = ar * QROWS + (tid >> 3);
        const __nv_bfloat16* wp = wq + (size_t)row0 * QCOLS + (tid & 7) * 8;
        uint4 w[6];
#pragma unroll
        for (int i = 0; i < 6; i++) w[i] = ldg_nc128(wp + cl * 64 + (size_t)i * 32 * QCOLS);
        float xv[6];
#pragma unroll
        for (int i = 0; i < 6; i++) xv[i] = __bfloat162float(x[row0 + i * 32]);
        static_assert(QLEAD == 2, "8 barriers");
        const uint32_t mybar = sb + (warp < 4 ? SA_BAR + (warp & 1) * 8 + (warp >> 1) * INBOX : SA_BARDEF + (warp - 4) * 8);
        if (lane == 0) {
            mbar_init(mybar, 1);
            if (warp < 5) mbar_init(sb + SA_BARGO + warp * 8, 1);
            asm volatile("fence.mbarrier_init.release.cluster;" ::: "memory");
        }
        __syncwarp();
        cluster_arrive_relaxed();
        if (lane == 0)
            mbar_expect_tx(mybar, warp < 4 ? ((warp & 1) ? ML_BYTES : warp == 0 ? MERGE_BYTES : MERGE_BYTES / 2)
                                           : warp == 4 ? NSR * 2 * 64 : warp == 5 ? 4 * WO_BOX : NAR * 8 * 256);
        __syncwarp();
        cluster_wait();
        int rnd = 0;
#pragma unroll 1
        for (int c = cl; c < NQITEM; c += ncl, rnd++) {
            if (rnd > 0) {
#pragma unroll
                for (int i = 0; i < 6; i++) w[i] = ldg_nc128(wp + c * 64 + (size_t)i * 32 * QCOLS);
            }
            float a[8];
#pragma unroll
            for (int k = 0; k < 8; k++) a[k] = 0.f;
#pragma unroll
            for (int i = 0; i < 6; i++) fma8(a, xv[i], w[i]);
            const bool u4 = lane & 16, u3 = lane & 8;
            float r4[4], r2[2];
#pragma unroll
            for (int k = 0; k < 4; k++)
                r4[k] = (u4 ? a[k + 4] : a[k]) + __shfl_xor_sync(0xffffffffu, u4 ? a[k] : a[k + 4], 16);
#pragma unroll
            for (int k = 0; k < 2; k++)
                r2[k] = (u3 ? r4[k + 2] : r4[k]) + __shfl_xor_sync(0xffffffffu, u3 ? r4[k] : r4[k + 2], 8);
            const int lead = rnd % NAR, lk = rnd / NAR;
            const uint32_t rb_ = mapa(sb, NSR + lead) + ((tag | cleared) & zero);
            st_async_v2(rb_ + SA_QRED + lk * (NAR * 8 * 256) + (ar * 8 + warp) * 256 + ((lane & 7) * 4 + (lane >> 3)) * 8,
                        __float_as_uint(r2[0]), __float_as_uint(r2[1]), rb_ + SA_BARQ + lk * 8);
            if (lead == ar) {
                if (warp == 0) {
                    mbar_wait(bar_qred + lk * 8, 0);
                    float s0 = 0.f, s1 = 0.f;
#pragma unroll
                    for (int k = 0; k < NAR * 8; k++) {
                        const float2 v = *reinterpret_cast<const float2*>(smem + SA_QRED + lk * (NAR * 8 * 256) + k * 256 + lane * 8);
                        s0 += v.x; s1 += v.y;
                    }
                    st_relaxed64(&sc->qpk[c * 32 + lane], (unsigned long long)pack_bf16(s0, s1) | ((unsigned long long)tag << 32));
                }
                named_sync(1, 256);
            }
            if (rnd == 0) {
                __nanosleep(2600);
                if (warp == 1) {
                    for (int r = aid + lane * ncl * NAR; r < D_MODEL; r += ncl * NAR * 32)
                        l2_prefetch(wq + (size_t)r * QCOLS + ncl * 64, (QCOLS - ncl * 64) * 2);
                    for (int r = DEF * NOWN + aid + lane * ncl * NAR; r < D_MODEL; r += ncl * NAR * 32)
                        l2_prefetch(wo + (size_t)r * QCOLS, QCOLS * 2);
                }
                __nanosleep(2000);
            }
        }
    }
    if (tid == 128) {
        asm volatile("fence.proxy.async.shared::cta;" ::: "memory");
#pragma unroll 1
        for (int k = 0; k < 4; k++)
            tma_load_2d(sb + SA_WO + k * WO_BOX, &wo_map48, ar * 192 + k * 48, (HKV - 1) * 256, sb + SA_BARWO);
    }
    __syncwarp();
    const int par = lane & 1;
    const bool has6 = 12 + par < ncl, has7 = 14 + par < ncl;
    auto combine = [&](const unsigned long long (&lo)[8], const unsigned long long (&hi)[8]) -> float2 {
        constexpr uint32_t mask = 0xffffffffu;
        float e[8];
#pragma unroll
        for (int k = 0; k < 8; k++) e[k] = __uint_as_float((uint32_t)lo[k]);
        if (!has6) e[6] = -INFINITY;
        if (!has7) e[7] = -INFINITY;
        float mx = fmaxf(fmaxf(fmaxf(e[0], e[1]), fmaxf(e[2], e[3])), fmaxf(fmaxf(e[4], e[5]), fmaxf(e[6], e[7])));
        mx = fmaxf(mx, __shfl_xor_sync(mask, mx, 1));
        float W = 0.f, o0 = 0.f, o1 = 0.f, W2 = 0.f, p0 = 0.f, p1 = 0.f;
#pragma unroll
        for (int k = 0; k < 8; k += 2) {
            const float wa = ex2(e[k] - mx), wb = ex2(e[k + 1] - mx);
            W += wa;
            o0 = fmaf(wa, __uint_as_float((uint32_t)(lo[k] >> 32)), o0);
            o1 = fmaf(wa, __uint_as_float((uint32_t)hi[k]), o1);
            W2 += wb;
            p0 = fmaf(wb, __uint_as_float((uint32_t)(lo[k + 1] >> 32)), p0);
            p1 = fmaf(wb, __uint_as_float((uint32_t)hi[k + 1]), p1);
        }
        W += W2; o0 += p0; o1 += p1;
        W += __shfl_xor_sync(mask, W, 1);
        o0 += __shfl_xor_sync(mask, o0, 1);
        o1 += __shfl_xor_sync(mask, o1, 1);
        const float inv = rcp(W);
        return make_float2(o0 * inv, o1 * inv);
    };
    uint4 wf[4][2][3];
    auto load_wf = [&]() {
        const uint32_t ab = sb + SA_WO + (warp >> 1) * WO_BOX +
                            ((warp & 1) * 128 + (lane >> 4) * 16 + ((lane >> 1) & 3) + (lane & 1) * 8) * 96 + ((lane >> 3) & 1) * 16;
        mbar_wait(sb + SA_BARWO, 0);
#pragma unroll
        for (int i = 0; i < 4; i++)
#pragma unroll
            for (int c = 0; c < 2; c++)
#pragma unroll
                for (int a = 0; a < 3; a++) wf[i][c][a] = ldsm_x4_trans(ab + ((i >> 1) * 64 + c * 32 + (i & 1) * 4) * 96 + a * 32);
    };
    const uint4* ysrc = hold(2 * warp + par < ncl ? &sc->ypk[aid < NOWN ? aid : 0][2 * warp + par][lane >> 1] : (const uint4*)nullptr);
    const uint32_t yst = hold(sb + SA_QRED + tid * 16);
    const uint32_t ba = hold(sb + SA_O + ((warp & 1) * 64 + (lane & 3) * 4) * 4), la = hold(sb + SA_LSE + (warp & 1) * 4);
    uint4* const ydst = hold(&sc->ypk[ar * 12 + (warp >> 1) * 3 + ((lane & 3) < 3 ? (lane & 3) : 0)][cl][(warp & 1) * 8 + (lane >> 2)]);
    __nv_bfloat16* const outp = hold(out + aid * 16 + (lane >> 1) + par * 8);
    const uint32_t role = hold((aid < NOWN ? 64 + warp : 0) | ((lane & 3) << 8));
    const uint32_t sbh = hold(sb), lane4 = hold(lane * 4);
    const uint32_t lsum_a = hold(sb + SA_ORED + (((lane >> 1) & 7) + par * 8) * LATE_N * 4);
    unsigned long long ylo[8], yhi[8];
    float wk[(NSLOT + 3) / 4 * 4];
    auto weights = [&](uint32_t ib) -> float {
        const uint32_t wb_addr = sb + SA_WT + warp * 128;
        float2 e = make_float2(-INFINITY, 0.f);
        if (lane < NSLOT) e = lds64f(ib + SA_ML + ((warp >> 1) * NSLOT + lane) * 8);
        float M = warp_max(e.x);
        const bool none = (M == -INFINITY);
        if (none) M = 0.f;
        const float wt = ex2((e.x - M) * SCL);
        float L = wt * e.y;
#pragma unroll
        for (int o = 16; o > 0; o >>= 1) L += __shfl_xor_sync(0xffffffffu, L, o);
        sts32(wb_addr + lane * 4, __float_as_uint(none ? 0.f : wt * rcp(L)));
        __syncwarp();
#pragma unroll
        for (int k = 0; k < (NSLOT + 3) / 4; k++) {
            const float4 w4 = lds128f(wb_addr + k * 16);
            wk[4 * k] = w4.x; wk[4 * k + 1] = w4.y; wk[4 * k + 2] = w4.z; wk[4 * k + 3] = w4.w;
        }
        __syncwarp();
        return none ? -INFINITY : fmaf(M, SCL, __log2f(L));
    };
    if (warp < 4) {
        float2* dst = &sc->part[ar][cl][tid];
        uint32_t ph = 0;
#pragma unroll 1
        for (int h = ar; h < HKV - 1; h += NAR, dst += NAR * MAX_CL * 128) {
            mbar_wait(sb + SA_BARML, ph);
            const float lse = weights(sb);
            if ((tid & 63) == 0) sts32(sb + SA_LSE + (warp >> 1) * 4, __float_as_uint(lse));
            mbar_wait(sb + SA_BAR, ph);
            ph ^= 1;
            float o0 = 0.f, o1 = 0.f;
#pragma unroll
            for (int k = 0; k < NSLOT; k++) {
                const float2 u = lds64f(sb + SA_SLOT + k * 1024 + tid * 8);
                o0 = fmaf(wk[k], u.x, o0);
                o1 = fmaf(wk[k], u.y, o1);
            }
            st_relaxed64(dst, (unsigned long long)__float_as_uint(o0) | ((unsigned long long)__float_as_uint(o1) << 32));
            named_sync(2, 128);
            if (warp == 0) {
                const bool again = h + NAR < HKV - 1;
                if (again && lane == 0) {
                    mbar_expect_tx(sb + SA_BAR, MERGE_BYTES);
                    mbar_expect_tx(sb + SA_BARML, ML_BYTES);
                }
                const float2 e = lds64f(sb + SA_LSE);
                __syncwarp();
                asm volatile("fence.acq_rel.gpu;" ::: "memory");
                if (lane < 2)
                    st_relaxed128(&sc->flag[h][cl][lane], (unsigned long long)__float_as_uint(e.x) | ((unsigned long long)__float_as_uint(e.y) << 32),
                                  (unsigned long long)tag << 32);
                if (again && lane < NSR)
                    asm volatile("mbarrier.arrive.relaxed.cluster.shared::cluster.b64 _, [%0];"
                                 ::"r"(mapa(sb + SS_BAR + (2 * STAGES + HKV + ar) * 8, lane)) : "memory");
                if (lane == 0) mbar_arrive(sb + SA_BARGO + (h / NAR) * 8);
            }
            named_sync(2, 128);
        }
    } else {
        if (aid < NOWN) {
#pragma unroll 1
            for (int h = ar; h < HKV - 1; h += NAR) {
                if (warp == 4) {
                    mbar_wait(sb + SA_BARGO + (h / NAR) * 8, 0);
                    __nanosleep(2000);
                    unsigned long long fl = 0, ft;
                    uint32_t n = 0;
                    while (true) {
                        ft = (unsigned long long)tag << 32;
                        if (lane < ncl) ld_acquire128(&sc->flag[h][lane][0], fl, ft);
                        if (__all_sync(0xffffffffu, (uint32_t)(ft >> 32) == tag)) break;
                        __nanosleep(500);
                        if (++n > SPIN_LIMIT) __trap();
                    }
                    if (lane < MAX_CL) {
                        sts32(sb + SA_FL + (h & 1) * 128 + lane * 4, (uint32_t)fl);
                        sts32(sb + SA_FL + (h & 1) * 128 + 64 + lane * 4, (uint32_t)(fl >> 32));
                    }
                }
                named_sync(5, 128);
#pragma unroll 1
                for (int qh = 0; qh < 2; qh++) {
                    const int pj = qh * 64 + (warp - 4) * 16 + (lane >> 1);
#pragma unroll
                    for (int k = 0; k < 8; k++) {
                        const int c = ((k < 6 || (k == 6 ? has6 : has7)) ? 2 * k : 0) + par;
                        const unsigned long long v = ld_relaxed64(&sc->part[h][c][pj]);
                        ylo[k] = lds32(sb + SA_FL + (h & 1) * 128 + qh * 64 + c * 4) | (v << 32);
                        yhi[k] = v >> 32;
                    }
                    const float2 o = combine(ylo, yhi);
                    const uint32_t rs = mapa(sb, h % NSR);
                    if (par == 0) st_async_b32(rs + SS_O + (h / NSR) * 512 + pj * 4, pack_bf16(o.x, o.y), rs + SS_BARO + (h / NSR) * 8);
                }
            }
        }
    }
    if (aid == 0 && tid == 128) *reinterpret_cast<volatile unsigned int*>(&sc->epoch) = tag;
    load_wf();
    const uint32_t ua = hold(sb + INBOX + SA_SLOT + tid * 4);
    const uint32_t oa = hold(sb + SA_O + ((tid & 65) | ((tid & 2) << 4) | ((tid & 60) >> 1)) * 4);
    const uint32_t t4 = role >> 8;
#pragma unroll 1
    for (uint32_t pass = zero; pass < 2; pass++) {
        const bool live = pass != 0;
        if (warp < 4) {
            if (live) mbar_wait(sbh + INBOX + SA_BARML, 0);
            const float lse = weights(sbh + INBOX);
            if ((tid & 63) == 0) sts32(sbh + SA_LSE + (warp >> 1) * 4, __float_as_uint(lse));
            if (live) mbar_wait(sbh + INBOX + SA_BAR, 0);
            uint32_t u[NSLOT];
#pragma unroll
            for (int k = 0; k < NSLOT; k++) u[k] = lds32(ua + k * 512);
            float o0 = 0.f, o1 = 0.f, p0 = 0.f, p1 = 0.f;
#pragma unroll
            for (int k = 0; k < NSLOT; k += 2) {
                o0 = fmaf(wk[k], bf_lo(u[k]), o0);         o1 = fmaf(wk[k], bf_hi(u[k]), o1);
                p0 = fmaf(wk[k + 1], bf_lo(u[k + 1]), p0); p1 = fmaf(wk[k + 1], bf_hi(u[k + 1]), p1);
            }
            sts32(oa, pack_bf16(o0 + p0, o1 + p1));
        }
        named_sync(3, 256);
        uint4 bo[4];
#pragma unroll
        for (int i = 0; i < 4; i++) bo[i] = lds128(ba + i * 64);
        const uint32_t lse = lds32(la);
        float d[3][2][4];
#pragma unroll
        for (int a = 0; a < 3; a++)
#pragma unroll
            for (int c = 0; c < 2; c++) d[a][c][0] = d[a][c][1] = d[a][c][2] = d[a][c][3] = 0.f;
#pragma unroll
        for (int i = 0; i < 4; i++)
#pragma unroll
            for (int c = 0; c < 2; c++)
#pragma unroll
                for (int a = 0; a < 3; a++)
                    mma_bf16(d[a][c], wf[i][c][a].x, wf[i][c][a].y, wf[i][c][a].z, wf[i][c][a].w, c ? bo[i].z : bo[i].x,
                             c ? bo[i].w : bo[i].y);
        const float y0 = t4 == 0 ? d[0][0][0] + d[0][1][0] : t4 == 1 ? d[1][0][0] + d[1][1][0] : d[2][0][0] + d[2][1][0];
        const float y1 = t4 == 0 ? d[0][0][2] + d[0][1][2] : t4 == 1 ? d[1][0][2] + d[1][1][2] : d[2][0][2] + d[2][1][2];
        if (t4 < 3)
            st_relaxed128(ydst, (unsigned long long)lse | ((unsigned long long)__float_as_uint(y0) << 32),
                          (unsigned long long)__float_as_uint(y1) | ((unsigned long long)(live ? tag : tag - 1u) << 32));
        if (role & 64u) {
            unsigned long long lo = 0xff800000ull, hi = (unsigned long long)tag << 32;
            uint32_t n = 0;
            while (live) {
                if (ysrc) ld_relaxed128(ysrc, lo, hi);
                if (__all_sync(0xffffffffu, (uint32_t)(hi >> 32) == tag)) break;
                if (++n > SPIN_LIMIT) __trap();
            }
            asm volatile("st.shared.v2.b64 [%0], {%1, %2};" ::"r"(yst), "l"(lo), "l"(hi) : "memory");
            if ((role & 7u) != 4) asm volatile("bar.arrive 6, 256;" ::: "memory");
        }
        if ((role & 255u) == 68) {
            named_sync(6, 256);
#pragma unroll
            for (int k = 0; k < 8; k++)
                asm volatile("ld.shared.v2.b64 {%0, %1}, [%2];" : "=l"(ylo[k]), "=l"(yhi[k]) : "r"(yst + (k - 4) * 512) : "memory");
            const float2 y = combine(ylo, yhi);
            float r = par ? y.y : y.x;
            r += __shfl_xor_sync(0xffffffffu, r, 16);
            if (live) mbar_wait(sbh + SA_BARDEF + (__float_as_uint(r) & zero), 0);
            const float4 l0 = lds128f(lsum_a), l1 = lds128f(lsum_a + 16);
            const float2 l2 = lds64f(lsum_a + 32);
            r += (((l0.x + l0.y) + (l0.z + l0.w)) + ((l1.x + l1.y) + (l1.z + l1.w))) + (l2.x + l2.y);
            if (live && lane4 < 64)
                asm volatile("st.global.b16 [%0], %1;" ::"l"(outp), "h"(__bfloat16_as_ushort(__float2bfloat16(r))) : "memory");
        }
        if (!live) named_sync(3, 256);
    }
}

constexpr int FB_SPLIT = 64;
__device__ float fb_q[QCOLS];
__device__ float fb_part[HQ][FB_SPLIT][DH + 2];
__device__ float fb_o[QCOLS];

__global__ void fb_q_kernel(const __nv_bfloat16* __restrict__ x, const __nv_bfloat16* __restrict__ wq) {
    const int c = blockIdx.x * blockDim.x + threadIdx.x;
    float a = 0.f;
    for (int i = 0; i < D_MODEL; i++) a = fmaf(__bfloat162float(x[i]), __bfloat162float(wq[(size_t)i * QCOLS + c]), a);
    fb_q[c] = __bfloat162float(__float2bfloat16(a));
}
__global__ void fb_attn_kernel(const __nv_bfloat16* __restrict__ kc, const __nv_bfloat16* __restrict__ vc) {
    const int sp = blockIdx.x, hq = blockIdx.y * 2 + (threadIdx.x >> 5), lane = threadIdx.x & 31;
    const size_t base = ((size_t)blockIdx.y * SK + (size_t)sp * (SK / FB_SPLIT)) * DH + lane * 4;
    const float4 q = *reinterpret_cast<const float4*>(&fb_q[hq * DH + lane * 4]);
    float m = -INFINITY, l = 0.f, a0 = 0.f, a1 = 0.f, a2 = 0.f, a3 = 0.f;
    for (int k = 0; k < SK / FB_SPLIT; k++) {
        const uint2 kv = *reinterpret_cast<const uint2*>(kc + base + (size_t)k * DH);
        const uint2 vv = *reinterpret_cast<const uint2*>(vc + base + (size_t)k * DH);
        float s = q.x * bf_lo(kv.x) + q.y * bf_hi(kv.x) + q.z * bf_lo(kv.y) + q.w * bf_hi(kv.y);
        for (int o = 16; o > 0; o >>= 1) s += __shfl_xor_sync(0xffffffffu, s, o);
        s *= 0.08838834764831845f;
        const float mn = fmaxf(m, s), al = __expf(m - mn), pw = __expf(s - mn);
        m = mn;
        l = l * al + pw;
        a0 = a0 * al + pw * bf_lo(vv.x); a1 = a1 * al + pw * bf_hi(vv.x);
        a2 = a2 * al + pw * bf_lo(vv.y); a3 = a3 * al + pw * bf_hi(vv.y);
    }
    float* dst = fb_part[hq][sp];
    dst[lane * 4] = a0; dst[lane * 4 + 1] = a1; dst[lane * 4 + 2] = a2; dst[lane * 4 + 3] = a3;
    if (lane == 0) { dst[DH] = m; dst[DH + 1] = l; }
}
__global__ void fb_combine_kernel() {
    const int hq = blockIdx.x, d = threadIdx.x;
    float M = -INFINITY, L = 0.f, a = 0.f;
    for (int s = 0; s < FB_SPLIT; s++) M = fmaxf(M, fb_part[hq][s][DH]);
    for (int s = 0; s < FB_SPLIT; s++) {
        const float w = __expf(fb_part[hq][s][DH] - M);
        L += w * fb_part[hq][s][DH + 1];
        a += w * fb_part[hq][s][d];
    }
    fb_o[hq * DH + d] = __bfloat162float(__float2bfloat16(a / L));
}
__global__ void fb_out_kernel(const __nv_bfloat16* __restrict__ wo, __nv_bfloat16* __restrict__ out) {
    const int c = blockIdx.x * blockDim.x + threadIdx.x;
    float a = 0.f;
    for (int i = 0; i < QCOLS; i++) a = fmaf(fb_o[i], __bfloat162float(wo[(size_t)i * D_MODEL + c]), a);
    out[c] = __float2bfloat16(a);
}

}

extern "C" void kernel_launch(void* const* d_in, const int* in_sizes, int n_in, void* d_out, int out_size) {
    (void)in_sizes; (void)n_in; (void)out_size;
    const __nv_bfloat16* x = (const __nv_bfloat16*)d_in[0];
    const __nv_bfloat16* kc = (const __nv_bfloat16*)d_in[1];
    const __nv_bfloat16* vc = (const __nv_bfloat16*)d_in[2];
    const __nv_bfloat16* wq = (const __nv_bfloat16*)d_in[3];
    const __nv_bfloat16* wo = (const __nv_bfloat16*)d_in[4];
    __nv_bfloat16* out = (__nv_bfloat16*)d_out;
    cudaStream_t stream = cudaStreamPerThread;

    cudaLaunchConfig_t cfg = {};
    cudaLaunchAttribute at[1];
    at[0].id = cudaLaunchAttributeClusterDimension;
    at[0].val.clusterDim.x = CL;
    at[0].val.clusterDim.y = 1;
    at[0].val.clusterDim.z = 1;
    cfg.attrs = at;
    cfg.numAttrs = 1;
    cfg.blockDim = dim3(NTHREADS);
    cfg.dynamicSmemBytes = SM_TOTAL;
    cfg.stream = stream;

    static int ncl = 0;
    static Scratch* scratch = nullptr;
    static CUtensorMap wo_map48;
    static const void* wo_mapped = nullptr;
    static bool maps_ok = false;
    if (ncl == 0) {
        int n = 0;
        cfg.gridDim = dim3(MAX_CL * CL);
        if (cudaFuncSetAttribute(gqa_decode_kernel, cudaFuncAttributeMaxDynamicSharedMemorySize, SM_TOTAL) != cudaSuccess ||
            cudaGetSymbolAddress((void**)&scratch, g_scratch) != cudaSuccess ||
            cudaOccupancyMaxActiveClusters(&n, gqa_decode_kernel, &cfg) != cudaSuccess) {
            (void)cudaGetLastError();
            n = 0;
        }
        ncl = n > MAX_CL ? MAX_CL : (n < MIN_CL ? -1 : n);
    }
    if (wo_mapped != (const void*)wo) {
        typedef CUresult (*EncodeFn)(CUtensorMap*, CUtensorMapDataType, cuuint32_t, void*, const cuuint64_t*,
                                     const cuuint64_t*, const cuuint32_t*, const cuuint32_t*, CUtensorMapInterleave,
                                     CUtensorMapSwizzle, CUtensorMapL2promotion, CUtensorMapFloatOOBfill);
        void* fn = nullptr;
        cudaDriverEntryPointQueryResult st;
        maps_ok = cudaGetDriverEntryPoint("cuTensorMapEncodeTiled", &fn, cudaEnableDefault, &st) == cudaSuccess && fn;
        const cuuint64_t gdim[2] = {(cuuint64_t)D_MODEL, (cuuint64_t)QCOLS};
        const cuuint64_t gstr[1] = {(cuuint64_t)D_MODEL * 2};
        const cuuint32_t box48[2] = {48, 256}, estr[2] = {1, 1};
        if (maps_ok)
            maps_ok = ((EncodeFn)fn)(&wo_map48, CU_TENSOR_MAP_DATA_TYPE_BFLOAT16, 2, d_in[4], gdim, gstr, box48, estr,
                                     CU_TENSOR_MAP_INTERLEAVE_NONE, CU_TENSOR_MAP_SWIZZLE_NONE,
                                     CU_TENSOR_MAP_L2_PROMOTION_L2_128B, CU_TENSOR_MAP_FLOAT_OOB_FILL_NONE) == CUDA_SUCCESS;
        wo_mapped = (const void*)wo;
    }
    if (ncl > 0 && maps_ok) {
        cfg.gridDim = dim3(ncl * CL);
        cudaLaunchKernelEx(&cfg, gqa_decode_kernel, ncl, 0u, kc, vc, wq, x, scratch, wo, out, wo_map48);
    } else {
        fb_q_kernel<<<QCOLS / 128, 128, 0, stream>>>(x, wq);
        fb_attn_kernel<<<dim3(FB_SPLIT, HKV), 64, 0, stream>>>(kc, vc);
        fb_combine_kernel<<<HQ, DH, 0, stream>>>();
        fb_out_kernel<<<D_MODEL / 64, 64, 0, stream>>>(wo, out);
    }
}
```
